```python
import torch

def _softmax(x, axis=-1):
    return torch.softmax(x, dim=axis)
def _gelu(x):
    return torch.nn.functional.gelu(x, approximate="tanh")
def _silu(x):
    return torch.nn.functional.silu(x)
def _sigmoid(x):
    return torch.sigmoid(x)
def _layernorm(x, axis=-1, eps=1e-5):
    m = x.mean(dim=axis, keepdim=True)
    v = x.var(dim=axis, keepdim=True, unbiased=False)
    return (x - m) / torch.sqrt(v + eps)
def _scatter_add(tgt, idx, src, axis=0):
    return tgt.clone().index_add_(axis, idx, src)
def _segment_sum(src, seg, n):
    out = torch.zeros((n,) + src.shape[1:], dtype=src.dtype)
    return out.index_add_(0, seg, src)
def _pad(x, pw):
    flat = tuple(v for pair in reversed(pw) for v in pair)
    return torch.nn.functional.pad(x, flat)

kernel_name = 'gated_mix__spectral_gfnet__ssm_conv_s4__prompt'

def setup_inputs():

    _w = (lambda a: (lambda t: t.to(torch.bfloat16) if t.is_floating_point() else t)(torch.as_tensor(a)))
    def _A_setup():
        B, S, D = 1, 2048, 448
        Df = D // 2 + 1
        return {
            "x": _w((lambda *s: torch.randn(*s, dtype=torch.bfloat16) * 0.05)(B, S, D)),
            "w_r": _w((lambda *s: torch.randn(*s, dtype=torch.bfloat16) * 0.8)(S, Df) * 0.02),
            "w_i": _w((lambda *s: torch.randn(*s, dtype=torch.bfloat16) * 0.8)(S, Df) * 0.02),
        }
    _A_in = _A_setup()

    def _B_setup():
        B, L, D, N = 1, 2048, 448, 256
        A_re = -(lambda _x: torch.exp(torch.as_tensor(_x)))((lambda *s: torch.randn(*s, dtype=torch.bfloat16) * 3.2)(D, N))
        A_im = torch.pi * (lambda *s: torch.randn(*s, dtype=torch.bfloat16) * 0.05)(D, N)
        B_re = (lambda *s: torch.randn(*s, dtype=torch.bfloat16) * 0.05)(D, N)
        B_im = (lambda *s: torch.randn(*s, dtype=torch.bfloat16) * 0.05)(D, N)
        C_re = (lambda *s: torch.randn(*s, dtype=torch.bfloat16) * 0.05)(D, N)
        C_im = (lambda *s: torch.randn(*s, dtype=torch.bfloat16) * 0.1)(D, N)
        log_dt = (lambda *s: torch.randn(*s, dtype=torch.bfloat16) * 0.05)(D) * 0.5 - 4.0
        Dskip = (lambda *s: torch.randn(*s, dtype=torch.bfloat16) * 0.05)(D)
        return {
            "u": _w((lambda *s: torch.randn(*s, dtype=torch.bfloat16) * 0.05)(B, L, D)),
            "A_re": _w(A_re),
            "A_im": _w(A_im),
            "B_re": _w(B_re),
            "B_im": _w(B_im),
            "C_re": _w(C_re),
            "C_im": _w(C_im),
            "log_dt": _w(log_dt),
            "Dskip": _w(Dskip),
        }
    _B_in = _B_setup()

    return {
        "A_x": _A_in["x"],
        "A_w_r": _A_in["w_r"],
        "A_w_i": _A_in["w_i"],
        "B_u": _B_in["u"],
        "B_A_re": _B_in["A_re"],
        "B_A_im": _B_in["A_im"],
        "B_B_re": _B_in["B_re"],
        "B_B_im": _B_in["B_im"],
        "B_C_re": _B_in["C_re"],
        "B_C_im": _B_in["C_im"],
        "B_log_dt": _B_in["log_dt"],
        "B_Dskip": _B_in["Dskip"],
        "gate_w": _w((lambda *s: torch.randn(*s, dtype=torch.bfloat16) * 0.05)(448) * 16.0),
    }

def reference(A_x, A_w_r, A_w_i, B_u, B_A_re, B_A_im, B_B_re, B_B_im, B_C_re, B_C_im, B_log_dt, B_Dskip, gate_w):
    def _A_ref(x, w_r, w_i):
        B, S, D = x.shape
        X = (lambda x, axes=(-2,-1): torch.fft.rfft2(x.float(), dim=axes))(x, axes=(-2, -1))
        W = w_r + 1j * w_i
        X = X * W
        y = (lambda x, s, axes=(-2,-1): torch.fft.irfft2(x, s=s, dim=axes).to(torch.bfloat16))(X, (S, D), axes=(-2, -1))
        return y

    def _B_ref(u, A_re, A_im, B_re, B_im, C_re, C_im, log_dt, Dskip):
        Bsz, L, D = u.shape
        dt = torch.exp(log_dt)[:, None]
        A = A_re + 1j * A_im
        Bc = B_re + 1j * B_im
        Cc = C_re + 1j * C_im
        logdA = dt * A
        dB = dt * Bc
        l = (lambda x, dt: x.to(dt))(torch.arange(L), A_re.dtype)
        P = torch.exp(logdA[:, :, None] * l[None, None, :])
        K = torch.einsum("dn,dnl,dn->dl", Cc, P, dB).real
        L2 = 2 * L
        Kp = _pad(K, ((0, 0), (0, L)))
        up = (lambda x, *d: x.permute(*d))(u, 0, 2, 1)
        up = _pad(up, ((0, 0), (0, 0), (0, L)))
        Kf = (lambda x, axes=(-2,-1): torch.fft.rfft2(x.float(), dim=axes))(Kp[:, None, :], axes=(-2, -1))
        Uf = (lambda x, axes=(-2,-1): torch.fft.rfft2(x.float(), dim=axes))(up[:, :, None, :], axes=(-2, -1))
        Yf = Uf * Kf[None, :, :, :]
        y = (lambda x, s, axes=(-2,-1): torch.fft.irfft2(x, s=s, dim=axes).to(torch.bfloat16))(Yf, (1, L2), axes=(-2, -1))[:, :, 0, :L]
        y = (lambda x, *d: x.permute(*d))(y, 0, 2, 1) + u * Dskip[None, None, :]
        return y

    x = A_x
    g = _sigmoid((x * gate_w).sum(-1, keepdims=True))
    a = _A_ref(x, A_w_r, A_w_i)
    b = _B_ref(x, B_A_re, B_A_im, B_B_re, B_B_im, B_C_re, B_C_im, B_log_dt, B_Dskip)
    return g * a + (1 - g) * b
```

```cpp
#include <cuda_runtime.h>
#include <cuda_bf16.h>
#include <cuda_fp16.h>
#include <stdint.h>

#define DEVI __device__ __forceinline__

DEVI uint32_t smem_u32(const void* p){ return (uint32_t)__cvta_generic_to_shared(p); }
DEVI uint32_t pack_bf16(float lo, float hi){ uint32_t r; asm("cvt.rn.bf16x2.f32 %0, %1, %2;" : "=r"(r) : "f"(hi), "f"(lo)); return r; }
DEVI uint32_t pack_f16(float lo, float hi){ uint32_t r; asm("cvt.rn.f16x2.f32 %0, %1, %2;" : "=r"(r) : "f"(hi), "f"(lo)); return r; }
DEVI float bf_lo(uint32_t w){ return __uint_as_float(w<<16); }
DEVI float bf_hi(uint32_t w){ return __uint_as_float(w & 0xffff0000u); }
DEVI uint32_t h2mul(uint32_t a, uint32_t b){ uint32_t r; asm("mul.rn.f16x2 %0,%1,%2;" : "=r"(r) : "r"(a),"r"(b)); return r; }
DEVI uint32_t h2fma(uint32_t a, uint32_t b, uint32_t c){ uint32_t r; asm("fma.rn.f16x2 %0,%1,%2,%3;" : "=r"(r) : "r"(a),"r"(b),"r"(c)); return r; }
DEVI uint32_t h2neg(uint32_t a){ uint32_t r; asm("neg.f16x2 %0,%1;" : "=r"(r) : "r"(a)); return r; }
struct C2 { uint32_t r, i; };
DEVI C2 cmul2(C2 a, C2 b){ C2 o; o.r = h2fma(a.r,b.r,h2neg(h2mul(a.i,b.i))); o.i = h2fma(a.r,b.i,h2mul(a.i,b.r)); return o; }

DEVI void mma_f16(float* d, uint32_t a0,uint32_t a1,uint32_t a2,uint32_t a3,uint32_t b0,uint32_t b1){
  asm volatile("mma.sync.aligned.m16n8k16.row.col.f32.f16.f16.f32 {%0,%1,%2,%3},{%4,%5,%6,%7},{%8,%9},{%0,%1,%2,%3};"
    : "+f"(d[0]),"+f"(d[1]),"+f"(d[2]),"+f"(d[3]) : "r"(a0),"r"(a1),"r"(a2),"r"(a3),"r"(b0),"r"(b1));
}
DEVI void mma_bf16(float* d, uint32_t a0,uint32_t a1,uint32_t a2,uint32_t a3,uint32_t b0,uint32_t b1){
  asm volatile("mma.sync.aligned.m16n8k16.row.col.f32.bf16.bf16.f32 {%0,%1,%2,%3},{%4,%5,%6,%7},{%8,%9},{%0,%1,%2,%3};"
    : "+f"(d[0]),"+f"(d[1]),"+f"(d[2]),"+f"(d[3]) : "r"(a0),"r"(a1),"r"(a2),"r"(a3),"r"(b0),"r"(b1));
}
DEVI void ldsm_x4(uint32_t& r0,uint32_t& r1,uint32_t& r2,uint32_t& r3, uint32_t addr){
  asm volatile("ldmatrix.sync.aligned.m8n8.x4.shared.b16 {%0,%1,%2,%3},[%4];" : "=r"(r0),"=r"(r1),"=r"(r2),"=r"(r3) : "r"(addr) : "memory");
}
DEVI void ldsm_x4t(uint32_t& r0,uint32_t& r1,uint32_t& r2,uint32_t& r3, uint32_t addr){
  asm volatile("ldmatrix.sync.aligned.m8n8.x4.trans.shared.b16 {%0,%1,%2,%3},[%4];" : "=r"(r0),"=r"(r1),"=r"(r2),"=r"(r3) : "r"(addr) : "memory");
}
DEVI void ldsm_x2(uint32_t& r0,uint32_t& r1, uint32_t addr){
  asm volatile("ldmatrix.sync.aligned.m8n8.x2.shared.b16 {%0,%1},[%2];" : "=r"(r0),"=r"(r1) : "r"(addr) : "memory");
}
DEVI uint32_t lds32(uint32_t a){ uint32_t v; asm volatile("ld.shared.b32 %0,[%1];" : "=r"(v) : "r"(a) : "memory"); return v; }
DEVI float ldsf(uint32_t a){ float v; asm volatile("ld.shared.f32 %0,[%1];" : "=f"(v) : "r"(a) : "memory"); return v; }
DEVI uint32_t lds16(uint32_t a){ uint16_t v; asm volatile("ld.shared.u16 %0,[%1];" : "=h"(v) : "r"(a) : "memory"); return v; }
DEVI uint2 lds64(uint32_t a){ uint2 v; asm volatile("ld.shared.v2.b32 {%0,%1},[%2];" : "=r"(v.x),"=r"(v.y) : "r"(a) : "memory"); return v; }
DEVI uint4 lds128(uint32_t a){ uint4 v; asm volatile("ld.shared.v4.b32 {%0,%1,%2,%3},[%4];" : "=r"(v.x),"=r"(v.y),"=r"(v.z),"=r"(v.w) : "r"(a) : "memory"); return v; }
DEVI void sts32(uint32_t a, uint32_t v){ asm volatile("st.shared.b32 [%0],%1;" :: "r"(a),"r"(v) : "memory"); }
DEVI void stsf(uint32_t a, float v){ asm volatile("st.shared.f32 [%0],%1;" :: "r"(a),"f"(v) : "memory"); }
DEVI void sts16(uint32_t a, uint32_t v){ asm volatile("st.shared.u16 [%0],%1;" :: "r"(a),"h"((uint16_t)v) : "memory"); }
DEVI void sts64(uint32_t a, uint32_t x, uint32_t y){ asm volatile("st.shared.v2.b32 [%0],{%1,%2};" :: "r"(a),"r"(x),"r"(y) : "memory"); }
DEVI void sts64f(uint32_t a, float x, float y){ asm volatile("st.shared.v2.f32 [%0],{%1,%2};" :: "r"(a),"f"(x),"f"(y) : "memory"); }
DEVI void sts128(uint32_t a, uint32_t x, uint32_t y, uint32_t z, uint32_t w){ asm volatile("st.shared.v4.b32 [%0],{%1,%2,%3,%4};" :: "r"(a),"r"(x),"r"(y),"r"(z),"r"(w) : "memory"); }
DEVI void bar_sync(int id, int n){ asm volatile("bar.sync %0,%1;" :: "r"(id),"r"(n) : "memory"); }
DEVI void cp_async8(uint32_t dst, const void* src){ asm volatile("cp.async.ca.shared.global [%0],[%1],8;" :: "r"(dst),"l"(src) : "memory"); }
DEVI void cp_async16(uint32_t dst, const void* src){ asm volatile("cp.async.cg.shared.global [%0],[%1],16;" :: "r"(dst),"l"(src) : "memory"); }
DEVI void cp_commit(){ asm volatile("cp.async.commit_group;" ::: "memory"); }
template<int N> DEVI void cp_wait(){ asm volatile("cp.async.wait_group %0;" :: "n"(N) : "memory"); }
DEVI void fence_async(){ asm volatile("fence.proxy.async.shared::cta;" ::: "memory"); }
DEVI void wg_fence(){ asm volatile("wgmma.fence.sync.aligned;" ::: "memory"); }
DEVI void wg_commit(){ asm volatile("wgmma.commit_group.sync.aligned;" ::: "memory"); }
template<int N> DEVI void wg_wait(){ asm volatile("wgmma.wait_group.sync.aligned %0;" :: "n"(N) : "memory"); }
DEVI uint64_t make_desc(uint32_t addr, uint32_t lbo, uint32_t sbo){
  return (uint64_t)((addr & 0x3FFFF)>>4) | ((uint64_t)(lbo>>4)<<16) | ((uint64_t)(sbo>>4)<<32);
}
DEVI void wgmma_rs_n32(float* d, uint32_t a0,uint32_t a1,uint32_t a2,uint32_t a3, uint64_t desc){
  asm volatile("wgmma.mma_async.sync.aligned.m64n32k16.f32.bf16.bf16 {%0,%1,%2,%3,%4,%5,%6,%7,%8,%9,%10,%11,%12,%13,%14,%15},{%16,%17,%18,%19},%20,1,1,1,0;"
   : "+f"(d[0]),"+f"(d[1]),"+f"(d[2]),"+f"(d[3]),"+f"(d[4]),"+f"(d[5]),"+f"(d[6]),"+f"(d[7]),"+f"(d[8]),"+f"(d[9]),"+f"(d[10]),"+f"(d[11]),"+f"(d[12]),"+f"(d[13]),"+f"(d[14]),"+f"(d[15])
   : "r"(a0),"r"(a1),"r"(a2),"r"(a3),"l"(desc));
}
DEVI void st_glb128(void* p, uint32_t x,uint32_t y,uint32_t z,uint32_t w){
  asm volatile("{ .reg .b128 t; .reg .b64 lo,hi; mov.b64 lo,{%1,%2}; mov.b64 hi,{%3,%4}; mov.b128 t,{lo,hi}; st.relaxed.gpu.global.b128 [%0], t; }" :: "l"(p),"r"(x),"r"(y),"r"(z),"r"(w) : "memory");
}


namespace pb {
constexpr int UC_PITCH = 656;
constexpr int UC_BYTES = 8*656;
constexpr int SEED_WARP = 6656;
constexpr int AREA = 4*SEED_WARP;
constexpr int OFF_PW = 3200;
constexpr int PW0 = 64;
constexpr int OFF_R4 = 5760, OFF_R8 = 6144;
constexpr int OFF_KC = 6528;
constexpr int OFF_Z2 = SEED_WARP + 3200;
constexpr int OFF_Z3 = 16640;
constexpr int OFF_YF = 20992;
constexpr int Z2P = 196*4, Z3P = 68*4;
constexpr int OFF_Y3 = 0;
constexpr int AREA2 = 32768;
constexpr int OFF_Y3B = 27520;
constexpr int WG_BYTES = UC_BYTES + AREA2;
constexpr int SM_RAW = 0;
constexpr int SM_SCALE = 16384;
constexpr int SM_MAP = SM_SCALE+128;
constexpr int SM_WG = SM_MAP + 3072;
constexpr int SM_TOTAL = SM_WG + 4*WG_BYTES;

struct MapT { uint32_t v[768]; };
constexpr int rbf_c(int l){
  int sh=0; while((l>>sh)>=256) sh++;
  if(sh==0) return l;
  int q=l>>sh, rem=l&((1<<sh)-1), half=1<<(sh-1);
  if(rem>half || (rem==half && (q&1))) q++;
  return q<<sh;
}
constexpr int slot_c(int r){
  int m=0,n=0;
  if(r<=512){ int q=r-1; m=q>>4; n=q&15; }
  else { const int a[8]={516,520,524,528,1032,1040,1544,1552}; for(int j=0;j<8;j++){ int dd=r-a[j]; if(dd>=0 && dd<512 && (dd&15)==0){ n=16+j; m=dd>>4; } } }
  int mt=m>>4, rr=m&15, g=rr&7, f=rr>>3, nt=n>>3, cc=n&7;
  int reg=(mt*3+nt)*4+2*f+(cc&1);
  return reg*32+4*g+(cc>>1);
}
constexpr MapT make_map(){
  MapT m{};
  for(int e=0;e<768;e++){ int src=0,dst=0;
    if(e<512){ int l=e+1; src=slot_c(rbf_c(l))*4; dst=OFF_PW+(l+PW0)*4; }
    else { int jj=e-512; int t8=jj>>7; jj&=127; src=slot_c((t8?8:4)*(129+jj))*4; dst=(t8?OFF_R8:OFF_R4)+(16+(jj>>1))*4+(jj&1)*2; }
    m.v[e]=(uint32_t)src|((uint32_t)dst<<16); }
  return m;
}
__device__ const MapT g_mapc = make_map();

DEVI float ex2f(float x){ float r; asm("ex2.approx.ftz.f32 %0,%1;" : "=f"(r) : "f"(x)); return r; }
DEVI float sinaf(float x){ float r; asm("sin.approx.ftz.f32 %0,%1;" : "=f"(r) : "f"(x)); return r; }
DEVI float cosaf(float x){ float r; asm("cos.approx.ftz.f32 %0,%1;" : "=f"(r) : "f"(x)); return r; }
DEVI void cexp_n(float L, float ph, float n, float& er, float& ei){
  float mag = ex2f(L*n);
  float p = ph*n; p -= rintf(p); p *= 6.283185307179586f;
  er = mag*cosaf(p); ei = mag*sinaf(p);
}
DEVI void csq(float r, float i, float& orr, float& oi){ float a=fmaf(r,r,-i*i); oi = (r+r)*i; orr=a; }

DEVI void kgen(uint32_t area, uint32_t sscale, int wid, int lane, float dt,
               uint32_t Are, uint32_t Aim, uint32_t Bre, uint32_t Bim, uint32_t Cre, uint32_t Cim){
  const int g=lane>>2, c=lane&3;
  float L[2],ph[2],cbr[2],cbi[2];
#pragma unroll
  for(int m=0;m<2;m++){
    float are=m?bf_hi(Are):bf_lo(Are), aim=m?bf_hi(Aim):bf_lo(Aim);
    float bre=dt*(m?bf_hi(Bre):bf_lo(Bre)), bim=dt*(m?bf_hi(Bim):bf_lo(Bim));
    float cre=m?bf_hi(Cre):bf_lo(Cre), cim=m?bf_hi(Cim):bf_lo(Cim);
    L[m]=(dt*are)*1.4426950408889634f; ph[m]=(dt*aim)*0.15915494309189535f;
    cbr[m]=cre*bre-cim*bim; cbi[m]=cre*bim+cim*bre;
  }
  float mx=fmaxf(fmaxf(fabsf(cbr[0]),fabsf(cbi[0])),fmaxf(fabsf(cbr[1]),fabsf(cbi[1])));
  uint32_t eb=__reduce_max_sync(0xffffffffu,__float_as_uint(mx))>>23;
  eb = min(max(eb,2u),252u);
  float up=__uint_as_float((eb+1)<<23), dn=__uint_as_float((253u-eb)<<23);
  cbr[0]*=dn; cbr[1]*=dn; cbi[0]*=dn; cbi[1]*=dn;
  float k0=cbr[0]+cbr[1];
#pragma unroll
  for(int o=16;o;o>>=1) k0+=__shfl_xor_sync(0xffffffffu,k0,o);
  float pr[2],pi[2];
  C2 e1,e2,e4,e8,e16,e16c,e32c,e64c,e128c,e512,e1024,cb;
  cb.r=pack_f16(cbr[0],cbr[1]); cb.i=pack_f16(cbi[0],cbi[1]);
#define PK(dst) { dst.r=pack_f16(pr[0],pr[1]); dst.i=pack_f16(pi[0],pi[1]); }
#define PKC(dst) { dst.r=pack_f16(pr[0],pr[1]); dst.i=pack_f16(-pi[0],-pi[1]); }
#define SQ() { csq(pr[0],pi[0],pr[0],pi[0]); csq(pr[1],pi[1],pr[1],pi[1]); }
  cexp_n(L[0],ph[0],1.f,pr[0],pi[0]); cexp_n(L[1],ph[1],1.f,pr[1],pi[1]);
  PK(e1); SQ(); PK(e2); SQ(); PK(e4); SQ(); PK(e8);
  cexp_n(L[0],ph[0],16.f,pr[0],pi[0]); cexp_n(L[1],ph[1],16.f,pr[1],pi[1]);
  PKC(e16c); e16.r=e16c.r; e16.i=e16c.i^0x80008000u;
  SQ(); PKC(e32c); SQ(); PKC(e64c); SQ(); PKC(e128c); SQ(); SQ(); PK(e512); SQ(); PK(e1024);
#undef PK
#undef PKC
#undef SQ
  const uint32_t wb = area + wid*SEED_WARP;
  const uint32_t fA = 2*(lane&3)+((lane>>2)&1);
  const uint32_t sA = wb + lane*128;
  {
    C2 one; one.r=0x3c003c00u; one.i=0u;
    C2 G3=cmul2(e16c,e32c);
    C2 F0=cmul2(cb,e1), F1=cmul2(cb,e2), F2=cmul2(F1,e1);
    C2 t;
    auto put=[&](int q, C2 G, C2 F){ sts128(sA+((q^fA)<<4),G.r,G.i,F.r,F.i); };
    put(0,one,F0); put(1,e16c,F1); put(2,e32c,F2); put(3,G3,cmul2(cb,e4));
    put(4,e64c,cmul2(F0,e4)); put(5,cmul2(e64c,e16c),cmul2(F1,e4)); put(6,cmul2(e64c,e32c),cmul2(F2,e4)); put(7,cmul2(e64c,G3),cmul2(cb,e8));
    (void)t;
    const uint32_t f2 = 2*((lane>>1)&1)+((lane>>2)&1);
    const uint32_t sF = wb + 4096 + lane*64;
    C2 f=cmul2(cb,e512), k=cmul2(cb,e1024);
    C2 a0=cmul2(f,e4), a1=cmul2(f,e8), a2=cmul2(a0,e8), a3=cmul2(f,e16);
    C2 b0=cmul2(k,e8), b1=cmul2(k,e16), b2=cmul2(b0,e512), b3=cmul2(b1,e512);
    sts128(sF+((0^f2)<<4),a0.r,a0.i,a1.r,a1.i); sts128(sF+((1^f2)<<4),a2.r,a2.i,a3.r,a3.i);
    sts128(sF+((2^f2)<<4),b0.r,b0.i,b1.r,b1.i); sts128(sF+((3^f2)<<4),b2.r,b2.i,b3.r,b3.i);
    sts128(wb+6144+lane*16,e8.r,e8.i,e128c.r,e128c.i);
  }
  __syncwarp();
  float acc[6][4];
#pragma unroll
  for(int i=0;i<6;i++){ acc[i][0]=acc[i][1]=acc[i][2]=acc[i][3]=0.f; }
  {
    uint32_t pa0=wb+c*128+((g^(2*c))<<4), pa1=wb+512+c*128+((g^(2*c+1))<<4);
    uint32_t pf0=wb+4096+c*64+(((g>>1)^(2*(c>>1)))<<4)+(g&1)*8, pf1=wb+4096+256+c*64+(((g>>1)^(2*(c>>1)+1))<<4)+(g&1)*8;
    uint32_t pe=wb+6144+c*16;
#pragma unroll 1
    for(int s=0;s<4;s++){
#pragma unroll
      for(int h=0;h<2;h++){
        uint4 A=lds128(h?pa1:pa0);
        uint2 B=lds64(h?pf1:pf0);
        uint4 E=lds128(pe+h*64);
        C2 G0={A.x,A.y}, F0={A.z,A.w}, c8={E.x,E.y}, c128={E.z,E.w};
        C2 G1=cmul2(G0,c128), F1=cmul2(F0,c8), G2=cmul2(G1,c128), G3=cmul2(G2,c128);
        mma_f16(acc[0],G0.r,G1.r,G0.i,G1.i,F0.r,F0.i);
        mma_f16(acc[1],G0.r,G1.r,G0.i,G1.i,F1.r,F1.i);
        mma_f16(acc[2],G0.r,G1.r,G0.i,G1.i,B.x,B.y);
        mma_f16(acc[3],G2.r,G3.r,G2.i,G3.i,F0.r,F0.i);
        mma_f16(acc[4],G2.r,G3.r,G2.i,G3.i,F1.r,F1.i);
        mma_f16(acc[5],G2.r,G3.r,G2.i,G3.i,B.x,B.y);
      }
      pa0+=1024; pa1+=1024; pf0+=512; pf1+=512; pe+=128;
    }
  }
  __syncwarp();
  const uint32_t sp = wb + lane*4;
#pragma unroll
  for(int i=0;i<6;i++)
#pragma unroll
    for(int j=0;j<4;j++) stsf(sp+(i*4+j)*128,acc[i][j]);
  if(lane==0){ stsf(wb+24*128,k0); stsf(sscale+wid*4,up); }
}

DEVI void kpost(uint32_t area, uint32_t sscale, uint32_t smap, int tid){
  uint4 sc4=lds128(sscale);
  float s0=__uint_as_float(sc4.x), s1=__uint_as_float(sc4.y), s2=__uint_as_float(sc4.z), s3=__uint_as_float(sc4.w);
#pragma unroll 2
  for(int e=tid;e<768;e+=128){
    uint32_t mp=lds32(smap+e*4);
    uint32_t src=area+(mp&0xffffu), dst=area+(mp>>16);
    float v=s0*ldsf(src)+s1*ldsf(src+SEED_WARP)+s2*ldsf(src+2*SEED_WARP)+s3*ldsf(src+3*SEED_WARP);
    uint32_t hb=pack_bf16(v,v);
    sts16(dst,hb);
    if(e<512) sts16(dst+6,hb);
    if(e==511) stsf(area+OFF_KC,v);
    if(e==639) stsf(area+OFF_KC+4,v);
  }
  if(tid==125){ const uint32_t src=area+24*128; float v=s0*ldsf(src)+s1*ldsf(src+SEED_WARP)+s2*ldsf(src+2*SEED_WARP)+s3*ldsf(src+3*SEED_WARP);
     uint32_t hb=pack_bf16(v,0.f); sts32(area+OFF_PW+PW0*4,hb&0xffffu); sts16(area+OFF_PW+(PW0+1)*4+2,hb); }
  if(tid<64) sts32(area+OFF_PW+tid*4,0u);
  if(tid<62) sts32(area+OFF_PW+(514+PW0+tid)*4,0u);
  if(tid==127) sts16(area+OFF_PW+(513+PW0)*4,0u);
  if(tid>=96 && tid<112){ int q=tid-96; sts32(area+OFF_R4+q*4,0u); sts32(area+OFF_R4+(80+q)*4,0u); sts32(area+OFF_R8+q*4,0u); sts32(area+OFF_R8+(80+q)*4,0u); }
}

DEVI uint32_t opq(uint32_t x, uint32_t sel){ uint32_t r; asm volatile("prmt.b32 %0,%1,%1,%2;" : "=r"(r) : "r"(x), "r"(sel)); return r; }
DEVI uint32_t uc_chunk(uint32_t uc, int m){ return uc + (m&7)*UC_PITCH + ((m>>3)+9)*16; }
DEVI uint32_t band_reg(int k0, int n, int lo, int hi){
  uint32_t a=((k0-n)>=lo && (k0-n)<=hi)?0x3f80u:0u, b=((k0+1-n)>=lo && (k0+1-n)<=hi)?0x3f800000u:0u; return a|b;
}
DEVI void win_tile(uint32_t a_addr0, uint32_t a_addr1, const uint32_t (&ba)[4], const uint32_t (&bb)[4], uint32_t dst, uint32_t zp){
    uint32_t a0,a1,a2,a3,a4,a5,a6,a7;
    ldsm_x4(a0,a1,a2,a3,a_addr0);
    ldsm_x4(a4,a5,a6,a7,a_addr1);
    float wa[4]={0,0,0,0}, wb[4]={0,0,0,0};
    mma_bf16(wa,a0,a1,a2,a3,ba[0],ba[1]); mma_bf16(wb,a0,a1,a2,a3,bb[0],bb[1]);
    mma_bf16(wa,a4,a5,a6,a7,ba[2],ba[3]); mma_bf16(wb,a4,a5,a6,a7,bb[2],bb[3]);
    sts32(dst,pack_bf16(wa[0],wb[0])); sts32(dst+zp,pack_bf16(wa[1],wb[1]));
    sts32(dst+32,pack_bf16(wa[2],wb[2])); sts32(dst+zp+32,pack_bf16(wa[3],wb[3]));
}
DEVI void windows(uint32_t uc, uint32_t area, int rho, int lane){
  const int g=lane>>2, c=lane&3;
  const int arow=(lane&7)+8*((lane>>3)&1), akc=lane>>4;
  const bool z3=(rho==2);
  const int loA=z3?13:11, hiA=z3?19:13, loB=z3?4:6, hiB=z3?12:10;
  uint32_t ba[4], bb[4];
#pragma unroll
  for(int q=0;q<4;q++){ ba[q]=band_reg(8*q+2*c,g,loA,hiA); bb[q]=band_reg(8*q+2*c,g,loB,hiB); }
  const uint32_t zp=z3?Z3P:Z2P;
  const int n=z3?8:6;
#pragma unroll 1
  for(int q=0;q<n;q++){
    const int mu=z3?(q>>1):(rho*6+q), h=z3?(q&1):0;
    const int m0=(z3? 2*(16*mu+arow)+h-3 : 16*mu+arow-2)+akc;
    win_tile(uc_chunk(uc,m0),uc_chunk(uc,m0+2),ba,bb,area+(z3?OFF_Z3:OFF_Z2)+(8*h+2*c)*zp+(16*mu+g)*4,zp);
  }
}
DEVI uint32_t yf_addr(uint32_t area, int t){ return area+OFF_YF+((t-512)+4*((t>>6)-8))*4; }
DEVI uint32_t y3_addr(uint32_t area, int t){ return area+OFF_Y3B+((t-1024)+4*((t>>6)-16))*4; }

DEVI void farjobs(uint32_t uc, uint32_t area, int rho, int lane, uint32_t id){
  const int g=lane>>2, c=lane&3;
  const int arow=(lane&7)+8*((lane>>3)&1), akc=lane>>4;
  const int njobs=(rho==2)?3:1;
#pragma unroll 1
  for(int q=0;q<njobs;q++){
    const bool f3=q>0;
    const int i0=(rho==2)?4:8+4*rho, h=f3?q-1:0;
    uint32_t qd[10][4];
    const uint32_t rb = area+(f3?OFF_R8:OFF_R4)+(g-c-48)*4;
#pragma unroll
    for(int t=0;t<10;t++){
      qd[t][0]=lds32(rb+(32-2*t)*16); qd[t][2]=lds32(rb+(31-2*t)*16);
      if(t==0){ qd[t][1]=lds32(rb+34*16); qd[t][3]=lds32(rb+33*16); }
      else { qd[t][1]=opq(qd[t-1][0],id); qd[t][3]=opq(qd[t-1][2],id); }
    }
    const uint32_t zp=f3?Z3P:Z2P;
    const float kc=ldsf(area+OFF_KC+(f3?4:0));
    float acc[4][4];
    {
      const int lo=f3?4:6;
      uint32_t b0=band_reg(2*c,g,lo,lo+1), b1=band_reg(8+2*c,g,lo,lo+1);
#pragma unroll
      for(int j=0;j<4;j++){
        int sg=16*(i0+j)+arow;
        int m0=(f3? 2*(sg-64)+h-1 : sg-65)+akc;
        uint32_t a0,a1,a2,a3; ldsm_x4(a0,a1,a2,a3,uc_chunk(uc,m0));
        acc[j][0]=acc[j][1]=acc[j][2]=acc[j][3]=0.f;
        mma_bf16(acc[j],a0,a1,a2,a3,b0,b1);
        acc[j][0]*=kc; acc[j][1]*=kc; acc[j][2]*=kc; acc[j][3]*=kc;
      }
    }
    const int s0=2*i0-16;
    const uint32_t za=area+(f3?OFF_Z3:OFF_Z2)+((lane&7)+8*h)*zp+(lane>>3)*16+s0*32;
#pragma unroll
    for(int tau=0;tau<16;tau+=2){
      if(s0+tau>=0){
        uint32_t b0,b1,b2,b3; ldsm_x4(b0,b1,b2,b3,za+tau*32);
#pragma unroll
        for(int j=0;j<4;j++){
          const int t=tau-2*j;
          if(t>=0 && t<10){
            mma_bf16(acc[j],qd[t][0],qd[t][1],qd[t][2],qd[t][3],b0,b1);
            mma_bf16(acc[j],qd[t+1][0],qd[t+1][1],qd[t+1][2],qd[t+1][3],b2,b3);
          }
        }
      }
    }
#pragma unroll
    for(int j=0;j<4;j++){
      if(!f3){ int t0=8*(16*(i0+j)+g)+2*c; sts64f(yf_addr(area,t0),acc[j][0],acc[j][1]); sts64f(yf_addr(area,t0+64),acc[j][2],acc[j][3]); }
      else { int t0=16*(16*(i0+j)+g)+8*h+2*c; sts64f(y3_addr(area,t0),acc[j][0],acc[j][1]); sts64f(y3_addr(area,t0+128),acc[j][2],acc[j][3]); }
    }
  }
}

DEVI void nearconv(uint32_t uc, uint32_t area, int lane, float (&acc)[4][4][4], uint32_t id){
  const int g=lane>>2, c=lane&3;
#pragma unroll
  for(int i=0;i<4;i++)
#pragma unroll
    for(int J=0;J<4;J++){ acc[i][J][0]=acc[i][J][1]=acc[i][J][2]=acc[i][J][3]=0.f; }
  uint32_t pq=area+OFF_PW+(PW0+g-2*c)*4;
  uint32_t qa[4][4];
#pragma unroll
  for(int D=-3;D<0;D++){ uint32_t x0=lds32(pq+(2*D)*32), x1=lds32(pq+(2*D+1)*32), xm=lds32(pq+(2*D-1)*32); qa[D&3][0]=x0; qa[D&3][1]=x1; qa[D&3][2]=xm; qa[D&3][3]=opq(x0,id); }
  const uint32_t ub=uc+((lane>>3)&1)*UC_PITCH+((lane>>4)*8+(lane&7)+9)*16;
#pragma unroll 1
  for(int u=0;u<9;u++){
    const uint32_t bu=ub-u*16;
#pragma unroll
    for(int r=0;r<4;r++){
      const int Dn=r;
      uint32_t x0=lds32(pq+(8*u+2*r)*32), x1=lds32(pq+(8*u+2*r+1)*32);
      qa[Dn][2]=opq(qa[(Dn+3)&3][1],id); qa[Dn][0]=x0; qa[Dn][1]=x1; qa[Dn][3]=opq(x0,id);
      const int j=3-r;
      uint32_t b[8];
      ldsm_x4(b[0],b[1],b[2],b[3],bu+2*j*UC_PITCH);
      ldsm_x4(b[4],b[5],b[6],b[7],bu+2*j*UC_PITCH+256);
#pragma unroll
      for(int i=0;i<4;i++){
        const int sl=(r+1+i)&3;
#pragma unroll
        for(int J=0;J<4;J++) mma_bf16(acc[i][J],qa[sl][0],qa[sl][1],qa[sl][2],qa[sl][3],b[2*J],b[2*J+1]);
      }
    }
  }
}
}


namespace pa {
constexpr float TWO_PI = 6.283185307179586f;
template<int TA,int TB>
DEVI void wgmma_ss_n32(float* d, uint64_t da, uint64_t db, int accum){
  asm volatile("{ .reg .pred p; setp.ne.b32 p,%18,0;\n"
   "wgmma.mma_async.sync.aligned.m64n32k16.f32.bf16.bf16 {%0,%1,%2,%3,%4,%5,%6,%7,%8,%9,%10,%11,%12,%13,%14,%15},%16,%17,p,1,1,%19,%20; }"
   : "+f"(d[0]),"+f"(d[1]),"+f"(d[2]),"+f"(d[3]),"+f"(d[4]),"+f"(d[5]),"+f"(d[6]),"+f"(d[7]),"+f"(d[8]),"+f"(d[9]),"+f"(d[10]),"+f"(d[11]),"+f"(d[12]),"+f"(d[13]),"+f"(d[14]),"+f"(d[15])
   : "l"(da),"l"(db),"r"(accum),"n"(TA),"n"(TB));
}
DEVI void wgmma_rs_n32z(float* d, uint32_t a0,uint32_t a1,uint32_t a2,uint32_t a3, uint64_t db){
  asm volatile("{ .reg .pred p; setp.ne.b32 p,0,0;\n"
   "wgmma.mma_async.sync.aligned.m64n32k16.f32.bf16.bf16 {%0,%1,%2,%3,%4,%5,%6,%7,%8,%9,%10,%11,%12,%13,%14,%15},{%16,%17,%18,%19},%20,p,1,1,0; }"
   : "+f"(d[0]),"+f"(d[1]),"+f"(d[2]),"+f"(d[3]),"+f"(d[4]),"+f"(d[5]),"+f"(d[6]),"+f"(d[7]),"+f"(d[8]),"+f"(d[9]),"+f"(d[10]),"+f"(d[11]),"+f"(d[12]),"+f"(d[13]),"+f"(d[14]),"+f"(d[15])
   : "r"(a0),"r"(a1),"r"(a2),"r"(a3),"l"(db));
}
DEVI uint32_t movm(uint32_t x){ uint32_t r; asm volatile("movmatrix.sync.aligned.m8n8.trans.b16 %0,%1;" : "=r"(r) : "r"(x)); return r; }
DEVI void sc_rev(float rev, float& s, float& c){ sincospif(2.0f*rev,&s,&c); }

constexpr int XS_ROW=896;
constexpr int SM_XS   = 0;
constexpr int SM_M64  = 14336;
constexpr int SM_B16  = SM_M64+8192;
constexpr int YS_KC=528, YS_CLS=8*528+32;
constexpr int SM_YS   = SM_B16+1024;
constexpr int SM_END1 = SM_YS+4*YS_CLS;

DEVI void build_m64(uint32_t base, int tid, int nth){
  for(int idx=tid; idx<2048; idx+=nth){
    int kc=idx>>8, r=(idx>>2)&63, p=idx&3;
    int j=8*(r>>4)+(r&7), sn=(r>>3)&1;
    float v[2];
#pragma unroll
    for(int e=0;e<2;e++){ int d2=8*kc+2*p+e; int n=(d2*(2*j+1))&127; float s,c; sincospif(n*(1.0f/64.0f),&s,&c); v[e]=sn?s:c; }
    sts32(base+kc*1024+r*16+p*4,pack_bf16(v[0],v[1]));
  }
}
DEVI void build_b16(uint32_t base, int s2, bool inverse, int tid){
  if(tid<256){
    int kc=tid>>7, n=(tid>>2)&31, p=tid&3;
    float v[2];
#pragma unroll
    for(int e=0;e<2;e++){ int k=8*kc+2*p+e; int a=inverse?(n&15):k, b=inverse?k:(n&15);
      int m=((128*a+s2)*b)&2047; float s,c; sincospif(m*(1.0f/1024.0f),&s,&c); v[e]=(n<16)?c:(inverse?s:-s); }
    sts32(base+kc*512+n*16+p*4,pack_bf16(v[0],v[1]));
  }
}
DEVI void slot_info(int cls, int mir, int j, int& fnat, int& cj, float& wt){
  int phi = mir? ((64-j)&63) : j+1;
  int f=cls+7*phi;
  if(f<=224){ fnat=f; cj=0; } else { fnat=448-f; cj=1; }
  wt=1.f;
  if(cls==0){ wt = mir? (j==0?0.5f:0.f) : (j<=30?1.f:0.5f); }
}
}

namespace {
using namespace pa;
__device__ uint32_t g_T[16*8*4*128*8];
__device__ uint32_t g_T2[128*16*4*32*2];
__device__ uint4 g_ybP[128*448*2];
__global__ void __launch_bounds__(512,1) kP1(const __nv_bfloat16* __restrict__ x){
  extern __shared__ __align__(128) unsigned char smem[];
  const uint32_t sb=smem_u32(smem);
  const int tid=threadIdx.x, warp=tid>>5, lane=tid&31, g=lane>>2, c=lane&3, cls=tid>>7, w=warp&3;
  const int s2=blockIdx.x;
  for(int i=tid;i<896;i+=512){ int s1=i/56, m=i%56, d1=m>>3, J=m&7;
    cp_async16(sb+SM_XS+s1*XS_ROW+d1*128+((J^d1)<<4), x+(size_t)(128*s1+s2)*448+m*8); }
  cp_commit();
  build_m64(sb+SM_M64,tid,512);
  build_b16(sb+SM_B16,s2,false,tid);
  uint32_t A7[4];
  { int sel=g>>2, k7=g&3; float cs[2],sn[2];
#pragma unroll
    for(int e=0;e<2;e++){ int d1=2*c+e; float s,cc; sincospif((2.0f/7.0f)*((d1*k7)%7),&s,&cc); bool ok=d1<7; cs[e]=ok?cc:0.f; sn[e]=ok?-s:0.f; }
    uint32_t pc=pack_bf16(cs[0],cs[1]), ps=pack_bf16(sn[0],sn[1]);
    A7[0]=sel?0u:pc; A7[1]=sel?0u:ps; A7[2]=sel?pc:0u; A7[3]=sel?ps:0u; }
  const int J=warp&7;
  float twr[2],twi[2];
#pragma unroll
  for(int e=0;e<2;e++){ int d2=8*J+2*c+e; float rev=-(float)(d2*(g&3))/448.0f-(float)d2/128.0f; float s,cc; sincospif(2.0f*rev,&s,&cc); twr[e]=cc; twi[e]=s; }
  cp_wait<0>();
  __syncthreads();
  {
#pragma unroll
    for(int ii=0;ii<2;ii++){
      int pair0=(warp>>3)*4+2*ii;
      int mi=lane>>3, d1=min(lane&7,6);
      int s1=2*(pair0+(mi>>1))+(mi&1);
      uint32_t b0,b1,b2,b3;
      ldsm_x4t(b0,b1,b2,b3,sb+SM_XS+s1*XS_ROW+d1*128+((J^d1)<<4));
#pragma unroll
      for(int h=0;h<2;h++){
        float a[4]={0,0,0,0};
        mma_bf16(a,A7[0],A7[1],A7[2],A7[3],h?b2:b0,h?b3:b1);
        float r0=a[0]*twr[0]-a[2]*twi[0], i0=a[0]*twi[0]+a[2]*twr[0];
        float r1=a[1]*twr[1]-a[3]*twi[1], i1=a[1]*twi[1]+a[3]*twr[1];
        int srow=2*(pair0+h)+(g>>2);
        uint32_t dst=sb+SM_YS+(g&3)*YS_CLS+J*YS_KC+srow*16+4*c;
        sts32(dst,pack_bf16(r0,r1)); sts32(dst+256,pack_bf16(i0,i1));
      }
    }
  }
  fence_async();
  __syncthreads();
  float d[16];
  {
    uint64_t da=make_desc(sb+SM_M64,1024,128), db=make_desc(sb+SM_YS+cls*YS_CLS,YS_KC,128);
    wg_fence();
#pragma unroll
    for(int ks=0;ks<4;ks++) wgmma_ss_n32<0,0>(d,da+(uint64_t)((2*ks*1024)>>4),db+(uint64_t)((2*ks*YS_KC)>>4),ks);
    wg_commit(); wg_wait<0>();
  }
  const int j=8*w+g;
  uint32_t Ad[4],Am[4];
  {
    int fn,cjd,cjm; float wt; slot_info(cls,0,j,fn,cjd,wt); slot_info(cls,1,j,fn,cjm,wt);
    uint32_t md=cjd?0x80008000u:0u, mm=cjm?0x80008000u:0u;
#pragma unroll
    for(int t=0;t<2;t++){
      float dr[2],di[2],mr[2],mi_[2];
#pragma unroll
      for(int e=0;e<2;e++){ float P=d[4*t+e],T=d[4*t+2+e],R=d[4*(t+2)+e],Q=d[4*(t+2)+2+e]; dr[e]=P+Q; di[e]=R-T; mr[e]=P-Q; mi_[e]=R+T; }
      Ad[2*t]=pack_bf16(dr[0],dr[1]); Ad[2*t+1]=pack_bf16(di[0],di[1])^md;
      Am[2*t]=pack_bf16(mr[0],mr[1]); Am[2*t+1]=pack_bf16(mi_[0],mi_[1])^mm;
    }
  }
  float od[16],om[16];
  {
    uint64_t db=make_desc(sb+SM_B16,512,128);
    wg_fence();
    wgmma_rs_n32z(od,Ad[0],Ad[1],Ad[2],Ad[3],db);
    wgmma_rs_n32z(om,Am[0],Am[1],Am[2],Am[3],db);
    wg_commit(); wg_wait<0>();
  }
  const int q=j>>2, jj=j&3;
#pragma unroll
  for(int t=0;t<2;t++)
#pragma unroll
    for(int e=0;e<2;e++){
      int k1=8*t+2*c+e;
      uint32_t wd=pack_bf16(od[4*t+e]-od[4*(t+2)+2+e], od[4*(t+2)+e]+od[4*t+2+e]);
      uint32_t wm=pack_bf16(om[4*t+e]-om[4*(t+2)+2+e], om[4*(t+2)+e]+om[4*t+2+e]);
      *(uint2*)&g_T[(((((k1*8+q)*4+cls)*128+s2)*4+jj)*2)]=make_uint2(wd,wm);
    }
}

constexpr int W_ROW=96;
__global__ void __launch_bounds__(128,1) kP2(const __nv_bfloat16* __restrict__ wr, const __nv_bfloat16* __restrict__ wi){
  __shared__ __align__(128) unsigned char smem[2*128*W_ROW + 4*4096];
  const uint32_t sb=smem_u32(smem);
  const int tid=threadIdx.x, cls=tid>>5, lane=tid&31, g=lane>>2, c=lane&3;
  const int k1=blockIdx.x>>3, q=blockIdx.x&7;
  const int f0=max(28*q-3,0);
  const int mis=(k1*225+f0)&7;
  for(int i=tid;i<128*6*2;i+=128){ int arr=i/(128*6), r=(i/6)%128, ch=i%6;
    size_t eoff=(size_t)(k1+16*r)*225+f0-mis+ch*8;
    const __nv_bfloat16* src=(arr?wi:wr)+eoff;
    if(eoff+8<=2048*225) cp_async16(sb+arr*128*W_ROW+r*W_ROW+ch*16,src);
    else { for(int e=0;e<8;e++){ uint32_t v=(eoff+e<2048*225)?(uint32_t)__bfloat16_as_ushort(src[e]):0u; sts16(sb+arr*128*W_ROW+r*W_ROW+ch*16+e*2,v);} }
  }
  const uint32_t tb=sb+2*128*W_ROW+cls*4096;
  for(int i=lane;i<256;i+=32){ int s2=i>>1, hf=i&1; cp_async16(tb+s2*32+((hf^((s2>>2)&1))<<4), &g_T[((k1*8+q)*4+cls)*1024+s2*8+hf*4]); }
  cp_commit();
  uint32_t F8[4],F8i[4],Bc[2],Bs[2],Ic[2][2];
  { float v[8];
#pragma unroll
    for(int h=0;h<2;h++){ int a=c+4*h; float s,cc; sincospif((a*g&7)*0.25f,&s,&cc);
      F8[2*h]=pack_bf16(cc,s); F8[2*h+1]=pack_bf16(-s,cc); }
    float c0,s0,c1,s1; sincospif(((2*c)*g&7)*0.25f,&s0,&c0); sincospif(((2*c+1)*g&7)*0.25f,&s1,&c1);
    F8i[0]=pack_bf16(c0,c1); F8i[1]=pack_bf16(s0,s1); F8i[2]=pack_bf16(-s0,-s1); F8i[3]=pack_bf16(c0,c1);
#pragma unroll
    for(int h=0;h<2;h++){ float sa,ca,sb_,cb; sincospif(((8*h+2*c)*(2*g+1)&31)*(1.0f/16.0f),&sa,&ca); sincospif(((8*h+2*c+1)*(2*g+1)&31)*(1.0f/16.0f),&sb_,&cb);
      Bc[h]=pack_bf16(ca,cb); Bs[h]=pack_bf16(sa,sb_); }
#pragma unroll
    for(int h=0;h<2;h++){ int b=8*h+g; float sa,ca,sb_,cb; sincospif((b*(4*c+1)&31)*(1.0f/16.0f),&sa,&ca); sincospif((b*(4*c+3)&31)*(1.0f/16.0f),&sb_,&cb);
      Ic[h][0]=pack_bf16(ca,cb); Ic[h][1]=pack_bf16(sa,sb_); }
    (void)v;
  }
  float tr[4],ti[4];
#pragma unroll
  for(int u=0;u<4;u++){ int b=8*(u>>1)+2*c+(u&1); float s,cc; sincospif(-2.0f*((float)(b*g)/128.0f+(float)b/32.0f),&s,&cc); tr[u]=cc; ti[u]=s; }
  cp_wait<0>();
  __syncthreads();
  for(int jj=0;jj<4;jj++){
    const int j=4*q+jj;
    uint2 wv[4];
#pragma unroll
    for(int u=0;u<4;u++){ int s2=16*(c+4*(u&1))+8*(u>>1)+g; wv[u]=lds64(tb+s2*32+((((jj>>1)^((s2>>2)&1)))<<4)+(jj&1)*8); }
    uint32_t outw[2][4];
#pragma unroll
    for(int mir=0;mir<2;mir++){
      int fn,cj; float wt; slot_info(cls,mir,j,fn,cj,wt);
      float D1[2][4];
#pragma unroll
      for(int h=0;h<2;h++){ D1[h][0]=D1[h][1]=D1[h][2]=D1[h][3]=0.f; mma_bf16(D1[h],F8[0],F8[1],F8[2],F8[3], mir?wv[2*h].y:wv[2*h].x, mir?wv[2*h+1].y:wv[2*h+1].x); }
      float yr[4],yi[4];
#pragma unroll
      for(int u=0;u<4;u++){ float a=D1[u>>1][u&1], b=D1[u>>1][2+(u&1)]; yr[u]=a*tr[u]-b*ti[u]; yi[u]=a*ti[u]+b*tr[u]; }
      uint32_t a0=pack_bf16(yr[0],yr[1]), a1=pack_bf16(yi[0],yi[1]), a2=pack_bf16(yr[2],yr[3]), a3=pack_bf16(yi[2],yi[3]);
      float PR[4]={0,0,0,0}, TQ[4]={0,0,0,0};
      mma_bf16(PR,a0,a1,a2,a3,Bc[0],Bc[1]); mma_bf16(TQ,a0,a1,a2,a3,Bs[0],Bs[1]);
      float Er[2],Ei[2],Or[2],Oi[2];
#pragma unroll
      for(int e=0;e<2;e++){
        int jb=2*c+e;
        float P=PR[e],R=PR[2+e],T=TQ[e],Q=TQ[2+e];
        float x1r=P+Q,x1i=R-T,x2r=P-Q,x2i=R+T;
        int r1=g+8*(jb+1), r2=g+8*((16-jb)&15);
        uint32_t o=(mis+fn-f0)*2;
        float w1r=__uint_as_float(lds16(sb+r1*W_ROW+o)<<16), w1i=__uint_as_float(lds16(sb+128*W_ROW+r1*W_ROW+o)<<16);
        float w2r=__uint_as_float(lds16(sb+r2*W_ROW+o)<<16), w2i=__uint_as_float(lds16(sb+128*W_ROW+r2*W_ROW+o)<<16);
        float z1r=x1r*w1r-x1i*w1i, z1i=x1r*w1i+x1i*w1r, z2r=x2r*w2r-x2i*w2i, z2i=x2r*w2i+x2i*w2r;
        Er[e]=z1r+z2r; Ei[e]=z1i+z2i; Or[e]=z1r-z2r; Oi[e]=z1i-z2i;
      }
      a0=pack_bf16(Er[0],Er[1]); a1=pack_bf16(Ei[0],Ei[1]); a2=pack_bf16(-Oi[0],-Oi[1]); a3=pack_bf16(Or[0],Or[1]);
      float H[2][4];
#pragma unroll
      for(int h=0;h<2;h++){ H[h][0]=H[h][1]=H[h][2]=H[h][3]=0.f; mma_bf16(H[h],a0,a1,a2,a3,Ic[h][0],Ic[h][1]); }
      uint32_t mr[2],mi_[2];
#pragma unroll
      for(int h=0;h<2;h++){
        float hr[2],hi[2];
#pragma unroll
        for(int e=0;e<2;e++){ int u=2*h+e; float a=H[h][e], b=H[h][2+e]; hr[e]=a*tr[u]+b*ti[u]; hi[e]=b*tr[u]-a*ti[u]; }
        mr[h]=movm(pack_bf16(hr[0],hr[1])); mi_[h]=movm(pack_bf16(hi[0],hi[1]));
      }
#pragma unroll
      for(int h=0;h<2;h++){ float U[4]={0,0,0,0}; mma_bf16(U,F8i[0],F8i[1],F8i[2],F8i[3],mr[h],mi_[h]);
        outw[mir][2*h]=pack_bf16(U[0],U[2]); outw[mir][2*h+1]=pack_bf16(U[1],U[3]); }
    }
#pragma unroll
    for(int u=0;u<4;u++){ int s2=16*g+8*(u>>1)+2*c+(u&1); *(uint2*)&g_T2[((((s2*16+k1)*4+cls)*32+j)*2)]=make_uint2(outw[0][u],outw[1][u]); }
  }
}

constexpr int YT_S=64*16+16;
constexpr int SM3_BP = SM_YS;
constexpr int SM3_YT = SM3_BP+4*4096;
constexpr int SM3_END = SM3_YT+16*YT_S;
constexpr int SM3_YB = SM3_END;
constexpr int SM3_G = SM3_YB+448*32;
constexpr int SM3_OUT = SM3_G+128;
constexpr int SM3_TOT = SM3_OUT+16*896;
DEVI uint32_t bmul(uint32_t a, uint32_t b){ uint32_t r; asm("mul.rn.bf16x2 %0,%1,%2;" : "=r"(r) : "r"(a),"r"(b)); return r; }
DEVI uint32_t badd(uint32_t a, uint32_t b){ uint32_t r; asm("add.rn.bf16x2 %0,%1,%2;" : "=r"(r) : "r"(a),"r"(b)); return r; }
__global__ void __launch_bounds__(512,1) kP3(const __nv_bfloat16* __restrict__ x, const uint32_t* __restrict__ dskip, const uint32_t* __restrict__ gatew, __nv_bfloat16* __restrict__ out){
  extern __shared__ __align__(128) unsigned char smem[];
  const uint32_t sb=smem_u32(smem);
  const int tid=threadIdx.x, warp=tid>>5, lane=tid&31, g=lane>>2, c=lane&3, cls=tid>>7, w=warp&3;
  const int s2=blockIdx.x;
  for(int i=tid;i<896;i+=512){ int s1=i/56, m=i%56; cp_async16(sb+SM_XS+s1*XS_ROW+m*16, x+(size_t)(128*s1+s2)*448+m*8); }
  for(int i=tid;i<896;i+=512){ int d=i>>1, hf=i&1; cp_async16(sb+SM3_YB+d*32+(hf<<4), &g_ybP[(s2*448+d)*2+hf]); }
  cp_commit();
  build_m64(sb+SM_M64,tid,512);
  build_b16(sb+SM_B16,s2,true,tid);
  cp_wait<0>();
  __syncthreads();
  {
    float acc=0.f;
    for(int i=lane;i<224;i+=32){ uint32_t p=bmul(lds32(sb+SM_XS+warp*XS_ROW+i*4),gatew[i]); acc+=bf_lo(p)+bf_hi(p); }
#pragma unroll
    for(int o=16;o;o>>=1) acc+=__shfl_xor_sync(0xffffffffu,acc,o);
    if(lane==0){ float sv=__bfloat162float(__float2bfloat16(acc)); float gg=1.0f/(1.0f+expf(-sv)); gg=__bfloat162float(__float2bfloat16(gg));
      uint32_t gb=pack_bf16(gg,gg), ob=pack_bf16(1.0f-gg,1.0f-gg); sts32(sb+SM3_G+warp*4,gb); sts32(sb+SM3_G+64+warp*4,ob); }
  }
  const int j=8*w+g;
  uint2 u[4];
#pragma unroll
  for(int t=0;t<4;t++){ int k1=8*(t>>1)+2*c+(t&1); u[t]=*(const uint2*)&g_T2[((((s2*16+k1)*4+cls)*32+j)*2)]; }
  fence_async();
  __syncthreads();
  float od[16],om[16];
  {
    uint64_t db=make_desc(sb+SM_B16,512,128);
    wg_fence();
    wgmma_rs_n32z(od,__byte_perm(u[0].x,u[1].x,0x5410),__byte_perm(u[0].x,u[1].x,0x7632),__byte_perm(u[2].x,u[3].x,0x5410),__byte_perm(u[2].x,u[3].x,0x7632),db);
    wgmma_rs_n32z(om,__byte_perm(u[0].y,u[1].y,0x5410),__byte_perm(u[0].y,u[1].y,0x7632),__byte_perm(u[2].y,u[3].y,0x5410),__byte_perm(u[2].y,u[3].y,0x7632),db);
    wg_commit(); wg_wait<0>();
  }
  {
    int fn,cjd,cjm; float wd,wm; slot_info(cls,0,j,fn,cjd,wd); slot_info(cls,1,j,fn,cjm,wm);
    float sd=cjd?-wd:wd, sm_=cjm?-wm:wm;
    const uint32_t bp=sb+SM3_BP+cls*4096+g*16+4*c;
#pragma unroll
    for(int t=0;t<2;t++){
      float Er[2],Ei[2],Or[2],Oi[2];
#pragma unroll
      for(int e=0;e<2;e++){
        float dr=(od[4*t+e]-od[4*(t+2)+2+e])*wd, di=(od[4*(t+2)+e]+od[4*t+2+e])*sd;
        float mr=(om[4*t+e]-om[4*(t+2)+2+e])*wm, mi_=(om[4*(t+2)+e]+om[4*t+2+e])*sm_;
        Er[e]=dr+mr; Ei[e]=di+mi_; Or[e]=dr-mr; Oi[e]=di-mi_;
      }
      sts32(bp+(2*w)*512+t*128,     pack_bf16(Er[0],Er[1]));
      sts32(bp+(2*w)*512+(2+t)*128, pack_bf16(Ei[0],Ei[1]));
      sts32(bp+(2*w+1)*512+t*128,     pack_bf16(-Oi[0],-Oi[1]));
      sts32(bp+(2*w+1)*512+(2+t)*128, pack_bf16(Or[0],Or[1]));
    }
  }
  fence_async();
  bar_sync(1+cls,128);
  float d[16];
  {
    uint64_t da=make_desc(sb+SM_M64,128,1024), db=make_desc(sb+SM3_BP+cls*4096,512,128);
    wg_fence();
#pragma unroll
    for(int ks=0;ks<4;ks++) wgmma_ss_n32<1,1>(d,da+(uint64_t)((ks*256)>>4),db+(uint64_t)((ks*1024)>>4),ks);
    wg_commit(); wg_wait<0>();
  }
  {
    const float scale=2.0f/(2048.0f*448.0f);
#pragma unroll
    for(int f=0;f<2;f++){
      int d2=16*w+g+8*f; float s,cc; sincospif(2.0f*((float)(d2*cls)/448.0f+(float)d2/128.0f),&s,&cc); cc*=scale; s*=scale;
#pragma unroll
      for(int t=0;t<2;t++)
#pragma unroll
        for(int e=0;e<2;e++){ float vr=d[4*t+2*f+e], vi=d[4*(t+2)+2*f+e]; int s1=8*t+2*c+e;
          sts32(sb+SM3_YT+s1*YT_S+d2*16+cls*4, pack_bf16(vr*cc-vi*s, vr*s+vi*cc)); }
    }
  }
  __syncthreads();
  uint32_t B7[2][2];
#pragma unroll
  for(int nt=0;nt<2;nt++){ int d1=4*nt+(g>>1), e=g&1; float s,cc; sincospif((2.0f/7.0f)*((d1*c)%7),&s,&cc); if(d1>=7){ s=0.f; cc=0.f; }
    uint32_t v=pack_bf16(cc,(c==0)?0.f:-s); B7[nt][0]=e==0?v:0u; B7[nt][1]=e==1?v:0u; }
  const int perm[16]={0,4,8,12,1,5,9,13,2,6,10,14,3,7,11,15};
#pragma unroll
  for(int pp=0;pp<2;pp++){
    int D0=4*warp+2*pp;
    int mi=lane>>3; int s1=perm[(lane&7)+8*(mi&1)];
    uint32_t a0,a1,a2,a3; ldsm_x4(a0,a1,a2,a3,sb+SM3_YT+s1*YT_S+(D0+(mi>>1))*16);
    uint32_t yb0,yb1,yb2,yb3;
    { int nt=mi>>1, hf=mi&1, r=lane&7; int d=min(64*(4*nt+(r>>1))+D0+(r&1),447); ldsm_x4t(yb0,yb1,yb2,yb3,sb+SM3_YB+d*32+hf*16); }
#pragma unroll
    for(int nt=0;nt<2;nt++){
      float y[4]={0,0,0,0}; mma_bf16(y,a0,a1,a2,a3,B7[nt][0],B7[nt][1]);
      int d1=4*nt+c;
      if(d1<7){
#pragma unroll
        for(int f=0;f<2;f++){
          int s1r=perm[g+8*f]; int d=64*d1+D0;
          uint32_t a=pack_bf16(y[2*f],y[2*f+1]);
          uint32_t yb=nt?(f?yb3:yb2):(f?yb1:yb0);
          uint32_t xv=lds32(sb+SM_XS+s1r*XS_ROW+d*2);
          uint32_t b=badd(yb,bmul(xv,dskip[d>>1]));
          uint32_t o=badd(bmul(lds32(sb+SM3_G+s1r*4),a),bmul(lds32(sb+SM3_G+64+s1r*4),b));
          sts32(sb+SM3_OUT+s1r*896+d*2,o);
        }
      }
    }
  }
  __syncthreads();
  for(int i=tid;i<896;i+=512){ int s1=i/56, m=i%56; uint4 v=lds128(sb+SM3_OUT+s1*896+m*16); *(uint4*)(out+(size_t)(128*s1+s2)*448+m*8)=v; }
}

}
namespace {
using namespace pb;
__global__ void __launch_bounds__(512,1) kB(const __nv_bfloat16* __restrict__ x, const uint32_t* Are,const uint32_t* Aim,const uint32_t* Bre,const uint32_t* Bim,const uint32_t* Cre,const uint32_t* Cim,
                   const __nv_bfloat16* logdt, uint32_t tag, uint32_t id){
  extern __shared__ __align__(128) unsigned char smem[];
  const uint32_t sb=smem_u32(smem);
  const int tid=threadIdx.x, v=tid>>7, wt=tid&127, wid=wt>>5, lane=tid&31;
  const int d=4*blockIdx.x+v;
  const int pidx=d*128+wid*32+lane;
  uint32_t rAre=Are[pidx], rAim=Aim[pidx], rBre=Bre[pidx], rBim=Bim[pidx], rCre=Cre[pidx], rCim=Cim[pidx];
  float ldt=__bfloat162float(logdt[d]);
  for(int e=tid;e<768;e+=512) sts32(sb+SM_MAP+e*4,g_mapc.v[e]);
  const uint32_t uc=sb+SM_WG+v*WG_BYTES, area=uc+UC_BYTES, sscale=sb+SM_SCALE+v*16;
  if(wt<72) sts128(uc+(wt/9)*UC_PITCH+(wt%9)*16,0,0,0,0);
  float dt=__bfloat162float(__float2bfloat16(expf(ldt)));
#pragma unroll
  for(int i=0;i<4;i++){ int t=tid+512*i; cp_async8(sb+SM_RAW+t*8, x+(size_t)t*448+4*blockIdx.x); }
  cp_commit();
  kgen(area,sscale,wid,lane,dt,rAre,rAim,rBre,rBim,rCre,rCim);
  cp_wait<0>();
  __syncthreads();
  {
    uint4 p=lds128(sb+SM_RAW+tid*32), q=lds128(sb+SM_RAW+tid*32+16);
    uint2 xr[4]={{p.x,p.y},{p.z,p.w},{q.x,q.y},{q.z,q.w}};
    int m=tid>>1, hf=tid&1;
    uint32_t u0=sb+SM_WG+(m&7)*UC_PITCH+((m>>3)+9)*16+hf*8;
    sts64(u0,               __byte_perm(xr[0].x,xr[1].x,0x5410),__byte_perm(xr[2].x,xr[3].x,0x5410));
    sts64(u0+WG_BYTES,      __byte_perm(xr[0].x,xr[1].x,0x7632),__byte_perm(xr[2].x,xr[3].x,0x7632));
    sts64(u0+2*WG_BYTES,    __byte_perm(xr[0].y,xr[1].y,0x5410),__byte_perm(xr[2].y,xr[3].y,0x5410));
    sts64(u0+3*WG_BYTES,    __byte_perm(xr[0].y,xr[1].y,0x7632),__byte_perm(xr[2].y,xr[3].y,0x7632));
  }
  __syncthreads();
  kpost(area,sscale,sb+SM_MAP,wt);
  bar_sync(1+v,128);
  const int role=(wid-v)&3;

  if(role==0){
    float acc[4][4][4];
    nearconv(uc,area,lane,acc,id);
    bar_sync(1+v,128);
    const int g=lane>>2, c=lane&3;
#pragma unroll
    for(int i=0;i<4;i++){
#pragma unroll
      for(int e=0;e<2;e++){
        float y[2][4];
#pragma unroll
        for(int f=0;f<2;f++)
#pragma unroll
          for(int J=0;J<4;J++){
            int a=8*J+2*c+e, t=64*a+16*i+g+8*f; float val=acc[i][J][2*f+e];
            if(J>=1) val+=ldsf(yf_addr(area,t));
            if(J>=2) val+=ldsf(y3_addr(area,t));
            y[f][J]=val;
          }
        uint32_t w00=pack_bf16(y[0][0],y[0][1]), w01=pack_bf16(y[0][2],y[0][3]), w10=pack_bf16(y[1][0],y[1][1]), w11=pack_bf16(y[1][2],y[1][3]);
        bool odd=c&1;
        uint32_t s0=odd?w00:w10, s1=odd?w01:w11;
        uint32_t r0=__shfl_xor_sync(0xffffffffu,s0,1), r1=__shfl_xor_sync(0xffffffffu,s1,1);
        uint32_t u0=odd?r0:w00, u1=odd?r1:w01, u2=odd?w10:r0, u3=odd?w11:r1;
        u0=(u0&~1u)|tag;
        int s2=64*e+16*i+g+8*(c&1);
        st_glb128(&g_ybP[(s2*448+d)*2+(c>>1)],u0,u1,u2,u3);
      }
    }
  } else {
    windows(uc,area,role-1,lane);
    bar_sync(5+v,96);
    farjobs(uc,area,role-1,lane,id);
    bar_sync(1+v,128);
  }
}

}

extern "C" void kernel_launch(void* const* d_in, const int* in_sizes, int n_in, void* d_out, int out_size) {
  (void)in_sizes; (void)n_in; (void)out_size;
  const __nv_bfloat16* x=(const __nv_bfloat16*)d_in[0];
  const __nv_bfloat16* wr=(const __nv_bfloat16*)d_in[1];
  const __nv_bfloat16* wi=(const __nv_bfloat16*)d_in[2];
  static bool init=false;
  if(!init){
    cudaFuncSetAttribute(kP1,cudaFuncAttributeMaxDynamicSharedMemorySize,pa::SM_END1);
    cudaFuncSetAttribute(kP3,cudaFuncAttributeMaxDynamicSharedMemorySize,SM3_TOT);
    cudaFuncSetAttribute(kB,cudaFuncAttributeMaxDynamicSharedMemorySize,pb::SM_TOTAL);
    init=true;
  }
  cudaStream_t s=cudaStreamPerThread;
  kP1<<<128,512,pa::SM_END1,s>>>(x);
  kP2<<<128,128,0,s>>>(wr,wi);
  kB<<<112,512,pb::SM_TOTAL,s>>>(x,(const uint32_t*)d_in[4],(const uint32_t*)d_in[5],(const uint32_t*)d_in[6],(const uint32_t*)d_in[7],(const uint32_t*)d_in[8],(const uint32_t*)d_in[9],
      (const __nv_bfloat16*)d_in[10],0u,0x3210u);
  kP3<<<128,512,SM3_TOT,s>>>(x,(const uint32_t*)d_in[11],(const uint32_t*)d_in[12],(__nv_bfloat16*)d_out);
}
```

```cpp
#include <cuda_runtime.h>
#include <cuda_bf16.h>
#include <cuda_fp16.h>
#include <stdint.h>

#define DEVI __device__ __forceinline__
namespace {

DEVI uint32_t smem_u32(const void* p){ return (uint32_t)__cvta_generic_to_shared(p); }
DEVI uint32_t pack_bf16(float lo, float hi){ uint32_t r; asm("cvt.rn.bf16x2.f32 %0, %1, %2;" : "=r"(r) : "f"(hi), "f"(lo)); return r; }
DEVI uint32_t pack_f16(float lo, float hi){ uint32_t r; asm("cvt.rn.f16x2.f32 %0, %1, %2;" : "=r"(r) : "f"(hi), "f"(lo)); return r; }
DEVI float bf_lo(uint32_t w){ return __uint_as_float(w<<16); }
DEVI float bf_hi(uint32_t w){ return __uint_as_float(w & 0xffff0000u); }
DEVI uint32_t h2mul(uint32_t a, uint32_t b){ uint32_t r; asm("mul.rn.f16x2 %0,%1,%2;" : "=r"(r) : "r"(a),"r"(b)); return r; }
DEVI uint32_t h2fma(uint32_t a, uint32_t b, uint32_t c){ uint32_t r; asm("fma.rn.f16x2 %0,%1,%2,%3;" : "=r"(r) : "r"(a),"r"(b),"r"(c)); return r; }
DEVI uint32_t h2neg(uint32_t a){ uint32_t r; asm("neg.f16x2 %0,%1;" : "=r"(r) : "r"(a)); return r; }
DEVI uint32_t bmul(uint32_t a, uint32_t b){ uint32_t r; asm("mul.rn.bf16x2 %0,%1,%2;" : "=r"(r) : "r"(a),"r"(b)); return r; }
DEVI uint32_t badd(uint32_t a, uint32_t b){ uint32_t r; asm("add.rn.bf16x2 %0,%1,%2;" : "=r"(r) : "r"(a),"r"(b)); return r; }
struct C2 { uint32_t r, i; };
DEVI C2 cmul2(C2 a, C2 b){ C2 o; o.r = h2fma(a.r,b.r,h2neg(h2mul(a.i,b.i))); o.i = h2fma(a.r,b.i,h2mul(a.i,b.r)); return o; }
DEVI float ex2f(float x){ float r; asm("ex2.approx.ftz.f32 %0,%1;" : "=f"(r) : "f"(x)); return r; }
DEVI float sinaf(float x){ float r; asm("sin.approx.ftz.f32 %0,%1;" : "=f"(r) : "f"(x)); return r; }
DEVI float cosaf(float x){ float r; asm("cos.approx.ftz.f32 %0,%1;" : "=f"(r) : "f"(x)); return r; }
constexpr float PI2 = 6.283185307179586f;

DEVI void mma_f16(float* d, uint32_t a0,uint32_t a1,uint32_t a2,uint32_t a3,uint32_t b0,uint32_t b1){
  asm("mma.sync.aligned.m16n8k16.row.col.f32.f16.f16.f32 {%0,%1,%2,%3},{%4,%5,%6,%7},{%8,%9},{%0,%1,%2,%3};"
    : "+f"(d[0]),"+f"(d[1]),"+f"(d[2]),"+f"(d[3]) : "r"(a0),"r"(a1),"r"(a2),"r"(a3),"r"(b0),"r"(b1));
}
DEVI void mma_bf16(float* d, uint32_t a0,uint32_t a1,uint32_t a2,uint32_t a3,uint32_t b0,uint32_t b1){
  asm("mma.sync.aligned.m16n8k16.row.col.f32.bf16.bf16.f32 {%0,%1,%2,%3},{%4,%5,%6,%7},{%8,%9},{%0,%1,%2,%3};"
    : "+f"(d[0]),"+f"(d[1]),"+f"(d[2]),"+f"(d[3]) : "r"(a0),"r"(a1),"r"(a2),"r"(a3),"r"(b0),"r"(b1));
}
DEVI void mma_bf16z(float* d, uint32_t a0,uint32_t a1,uint32_t a2,uint32_t a3,uint32_t b0,uint32_t b1){
  asm("mma.sync.aligned.m16n8k16.row.col.f32.bf16.bf16.f32 {%0,%1,%2,%3},{%4,%5,%6,%7},{%8,%9},{%10,%10,%10,%10};"
    : "=f"(d[0]),"=f"(d[1]),"=f"(d[2]),"=f"(d[3]) : "r"(a0),"r"(a1),"r"(a2),"r"(a3),"r"(b0),"r"(b1),"f"(0.f));
}
DEVI void ldsm_x4(uint32_t& r0,uint32_t& r1,uint32_t& r2,uint32_t& r3, uint32_t addr){
  asm volatile("ldmatrix.sync.aligned.m8n8.x4.shared.b16 {%0,%1,%2,%3},[%4];" : "=r"(r0),"=r"(r1),"=r"(r2),"=r"(r3) : "r"(addr) : "memory");
}
DEVI void ldsm_x4t(uint32_t& r0,uint32_t& r1,uint32_t& r2,uint32_t& r3, uint32_t addr){
  asm volatile("ldmatrix.sync.aligned.m8n8.x4.trans.shared.b16 {%0,%1,%2,%3},[%4];" : "=r"(r0),"=r"(r1),"=r"(r2),"=r"(r3) : "r"(addr) : "memory");
}
DEVI uint32_t movm(uint32_t x){ uint32_t r; asm("movmatrix.sync.aligned.m8n8.trans.b16 %0,%1;" : "=r"(r) : "r"(x)); return r; }
DEVI uint32_t lds32(uint32_t a){ uint32_t v; asm volatile("ld.shared.b32 %0,[%1];" : "=r"(v) : "r"(a) : "memory"); return v; }
DEVI float ldsf(uint32_t a){ float v; asm volatile("ld.shared.f32 %0,[%1];" : "=f"(v) : "r"(a) : "memory"); return v; }
DEVI uint32_t lds16(uint32_t a){ uint16_t v; asm volatile("ld.shared.u16 %0,[%1];" : "=h"(v) : "r"(a) : "memory"); return v; }
DEVI uint2 lds64(uint32_t a){ uint2 v; asm volatile("ld.shared.v2.b32 {%0,%1},[%2];" : "=r"(v.x),"=r"(v.y) : "r"(a) : "memory"); return v; }
DEVI uint4 lds128(uint32_t a){ uint4 v; asm volatile("ld.shared.v4.b32 {%0,%1,%2,%3},[%4];" : "=r"(v.x),"=r"(v.y),"=r"(v.z),"=r"(v.w) : "r"(a) : "memory"); return v; }
DEVI void sts32(uint32_t a, uint32_t v){ asm volatile("st.shared.b32 [%0],%1;" :: "r"(a),"r"(v) : "memory"); }
DEVI void stsf(uint32_t a, float v){ asm volatile("st.shared.f32 [%0],%1;" :: "r"(a),"f"(v) : "memory"); }
DEVI void sts64(uint32_t a, uint32_t x, uint32_t y){ asm volatile("st.shared.v2.b32 [%0],{%1,%2};" :: "r"(a),"r"(x),"r"(y) : "memory"); }
DEVI void sts64f(uint32_t a, float x, float y){ asm volatile("st.shared.v2.f32 [%0],{%1,%2};" :: "r"(a),"f"(x),"f"(y) : "memory"); }
DEVI void sts128(uint32_t a, uint32_t x, uint32_t y, uint32_t z, uint32_t w){ asm volatile("st.shared.v4.b32 [%0],{%1,%2,%3,%4};" :: "r"(a),"r"(x),"r"(y),"r"(z),"r"(w) : "memory"); }
DEVI void bar_sync(int id, int n){ asm volatile("bar.sync %0,%1;" :: "r"(id),"r"(n) : "memory"); }
DEVI void bar_arrive(int id, int n){ asm volatile("bar.arrive %0,%1;" :: "r"(id),"r"(n) : "memory"); }
DEVI void mbar_init(uint32_t a, int n){ asm volatile("mbarrier.init.shared::cta.b64 [%0],%1;" :: "r"(a),"r"(n) : "memory"); }
DEVI void mbar_expect(uint32_t a, uint32_t bytes){ asm volatile("mbarrier.arrive.expect_tx.shared::cta.b64 _,[%0],%1;" :: "r"(a),"r"(bytes) : "memory"); }
DEVI void mbar_arrive(uint32_t a){ asm volatile("mbarrier.arrive.shared::cta.b64 _,[%0];" :: "r"(a) : "memory"); }
DEVI void mbar_wait(uint32_t a){
  asm volatile("{ .reg .pred p; .reg .u32 it; mov.u32 it,0;\n"
    "W_%=: mbarrier.try_wait.parity.shared::cta.b64 p,[%0],0,2000; @p bra D_%=; add.u32 it,it,1; setp.lt.u32 p,it,200000; @p bra W_%=;\n"
    "D_%=: }" :: "r"(a) : "memory");
}
DEVI void st_rlx128(void* p, uint32_t x,uint32_t y,uint32_t z,uint32_t w){
  asm volatile("{ .reg .b128 t; .reg .b64 lo,hi; mov.b64 lo,{%1,%2}; mov.b64 hi,{%3,%4}; mov.b128 t,{lo,hi}; st.relaxed.gpu.global.b128 [%0], t; }" :: "l"(p),"r"(x),"r"(y),"r"(z),"r"(w) : "memory");
}
DEVI uint4 ld_rlx128(const void* p){
  uint4 v;
  asm volatile("{ .reg .b128 t; .reg .b64 lo,hi; ld.relaxed.gpu.global.b128 t,[%4]; mov.b128 {lo,hi},t; mov.b64 {%0,%1},lo; mov.b64 {%2,%3},hi; }" : "=r"(v.x),"=r"(v.y),"=r"(v.z),"=r"(v.w) : "l"(p) : "memory");
  return v;
}
DEVI void cp_mbar_arrive(uint32_t mb){ asm volatile("cp.async.mbarrier.arrive.noinc.shared::cta.b64 [%0];" :: "r"(mb) : "memory"); }
DEVI void bulk_g2s(uint32_t dst, const void* src, uint32_t bytes, uint32_t mb){
  asm volatile("cp.async.bulk.shared::cluster.global.mbarrier::complete_tx::bytes [%0],[%1],%2,[%3];" :: "r"(dst),"l"(src),"r"(bytes),"r"(mb) : "memory");
}
DEVI void cp_async16(uint32_t dst, const void* src){ asm volatile("cp.async.cg.shared.global [%0],[%1],16;" :: "r"(dst),"l"(src) : "memory"); }
DEVI void cp_commit(){ asm volatile("cp.async.commit_group;" ::: "memory"); }
template<int N> DEVI void cp_wait(){ asm volatile("cp.async.wait_group %0;" :: "n"(N) : "memory"); }
DEVI void fence_async(){ asm volatile("fence.proxy.async.shared::cta;" ::: "memory"); }
DEVI void wg_fence(){ asm volatile("wgmma.fence.sync.aligned;" ::: "memory"); }
DEVI void wg_commit(){ asm volatile("wgmma.commit_group.sync.aligned;" ::: "memory"); }
template<int N> DEVI void wg_wait(){ asm volatile("wgmma.wait_group.sync.aligned %0;" :: "n"(N) : "memory"); }
DEVI uint64_t make_desc(uint32_t addr, uint32_t lbo, uint32_t sbo){
  return (uint64_t)((addr & 0x3FFFF)>>4) | ((uint64_t)(lbo>>4)<<16) | ((uint64_t)(sbo>>4)<<32);
}
template<int TA,int TB>
DEVI void wgmma_ss_n32(float* d, uint64_t da, uint64_t db, int accum){
  asm volatile("{ .reg .pred p; setp.ne.b32 p,%18,0;\n"
   "wgmma.mma_async.sync.aligned.m64n32k16.f32.bf16.bf16 {%0,%1,%2,%3,%4,%5,%6,%7,%8,%9,%10,%11,%12,%13,%14,%15},%16,%17,p,1,1,%19,%20; }"
   : "+f"(d[0]),"+f"(d[1]),"+f"(d[2]),"+f"(d[3]),"+f"(d[4]),"+f"(d[5]),"+f"(d[6]),"+f"(d[7]),"+f"(d[8]),"+f"(d[9]),"+f"(d[10]),"+f"(d[11]),"+f"(d[12]),"+f"(d[13]),"+f"(d[14]),"+f"(d[15])
   : "l"(da),"l"(db),"r"(accum),"n"(TA),"n"(TB));
}
DEVI void wgmma_rs_n32z(float* d, uint32_t a0,uint32_t a1,uint32_t a2,uint32_t a3, uint64_t db){
  asm volatile("{ .reg .pred p; setp.ne.b32 p,0,0;\n"
   "wgmma.mma_async.sync.aligned.m64n32k16.f32.bf16.bf16 {%0,%1,%2,%3,%4,%5,%6,%7,%8,%9,%10,%11,%12,%13,%14,%15},{%16,%17,%18,%19},%20,p,1,1,0; }"
   : "+f"(d[0]),"+f"(d[1]),"+f"(d[2]),"+f"(d[3]),"+f"(d[4]),"+f"(d[5]),"+f"(d[6]),"+f"(d[7]),"+f"(d[8]),"+f"(d[9]),"+f"(d[10]),"+f"(d[11]),"+f"(d[12]),"+f"(d[13]),"+f"(d[14]),"+f"(d[15])
   : "r"(a0),"r"(a1),"r"(a2),"r"(a3),"l"(db));
}
DEVI void wgmma_rs_n32(float* d, uint32_t a0,uint32_t a1,uint32_t a2,uint32_t a3, uint64_t db){
  asm volatile("wgmma.mma_async.sync.aligned.m64n32k16.f32.bf16.bf16 {%0,%1,%2,%3,%4,%5,%6,%7,%8,%9,%10,%11,%12,%13,%14,%15},{%16,%17,%18,%19},%20,1,1,1,0;"
   : "+f"(d[0]),"+f"(d[1]),"+f"(d[2]),"+f"(d[3]),"+f"(d[4]),"+f"(d[5]),"+f"(d[6]),"+f"(d[7]),"+f"(d[8]),"+f"(d[9]),"+f"(d[10]),"+f"(d[11]),"+f"(d[12]),"+f"(d[13]),"+f"(d[14]),"+f"(d[15])
   : "r"(a0),"r"(a1),"r"(a2),"r"(a3),"l"(db));
}
DEVI uint32_t opq(uint32_t x, uint32_t sel){ uint32_t r; asm("prmt.b32 %0,%1,%1,%2;" : "=r"(r) : "r"(x), "r"(sel)); return r; }

namespace ct {
constexpr double PI=3.14159265358979323846264338327950288;
constexpr double c_sin(double x){ double t=x, s=x; for(int i=1;i<16;i++){ t*=-x*x/((2*i)*(2*i+1)); s+=t; } return s; }
constexpr double c_cos(double x){ double t=1, s=1; for(int i=1;i<16;i++){ t*=-x*x/((2*i-1)*(2*i)); s+=t; } return s; }
constexpr double red(int n,int d){ int m=((n%d)+d)%d; if(2*m>d) m-=d; return 2*PI*m/d; }
constexpr double cosr(int n,int d){ int m=((n%d)+d)%d; if(4*m==d||4*m==3*d) return 0.0; return c_cos(red(n,d)); }
constexpr double sinr(int n,int d){ int m=((n%d)+d)%d; if(m==0||2*m==d) return 0.0; return c_sin(red(n,d)); }
constexpr uint32_t bf16(double v){
  if(v==0) return 0;
  uint32_t s=0; if(v<0){ s=0x8000; v=-v; }
  int e=0; while(v>=2){ v/=2; e++; } while(v<1){ v*=2; e--; }
  double m=(v-1)*128; uint32_t q=(uint32_t)m; double r=m-q; if(r>0.5 || (r==0.5 && (q&1))) q++;
  if(q==128){ q=0; e++; }
  return s|((uint32_t)(e+127)<<7)|q;
}
constexpr uint32_t pk(double lo,double hi){ return bf16(lo)|(bf16(hi)<<16); }
constexpr uint32_t band(int k0,int n,int lo,int hi){ return ((k0-n>=lo && k0-n<=hi)?0x3f80u:0u)|((k0+1-n>=lo && k0+1-n<=hi)?0x3f800000u:0u); }
constexpr int rbf(int l){ int sh=0; while((l>>sh)>=256) sh++; if(sh==0) return l; int q=l>>sh, rem=l&((1<<sh)-1), half=1<<(sh-1); if(rem>half || (rem==half && (q&1))) q++; return q<<sh; }
struct Tab {
  uint32_t m64[2048];
  uint32_t a7[128];
  float    tw1[1024];
  uint32_t p2c[512];
  float    tw2[256];
  float    tw3[512];
  uint32_t b7[128];
  uint32_t bandt[512];
  uint32_t corr[128];
  uint32_t pwmap[512];
};
constexpr Tab make(){
  Tab t{};
  for(int idx=0;idx<2048;idx++){ int kc=idx>>8, r=(idx>>2)&63, pp=idx&3, j2=2*(8*(r>>4)+(r&7))+1, d2=8*kc+2*pp; bool sn=(r>>3)&1;
    t.m64[idx]= sn? pk(sinr(d2*j2,128),sinr((d2+1)*j2,128)) : pk(cosr(d2*j2,128),cosr((d2+1)*j2,128)); }
  for(int l=0;l<32;l++){ int g=l>>2,c=l&3;
    { int sel=g>>2,k7=g&3; int d0=2*c,d1=2*c+1; uint32_t pc=pk(cosr(d0*k7,7), d1<7?cosr(d1*k7,7):0.0), ps=pk(-sinr(d0*k7,7), d1<7?-sinr(d1*k7,7):0.0);
      t.a7[4*l]=sel?0u:pc; t.a7[4*l+1]=sel?0u:ps; t.a7[4*l+2]=sel?pc:0u; t.a7[4*l+3]=sel?ps:0u; }
    for(int J=0;J<8;J++) for(int e=0;e<2;e++){ int d2=8*J+2*c+e, n=-d2*(2*(g&3)+7); t.tw1[(J*32+l)*4+2*e]=(float)cosr(n,896); t.tw1[(J*32+l)*4+2*e+1]=(float)sinr(n,896); }
    for(int h=0;h<2;h++){ int a=(c+4*h)*g; t.p2c[(0*32+l)*4+2*h]=pk(cosr(a,8),sinr(a,8)); t.p2c[(0*32+l)*4+2*h+1]=pk(-sinr(a,8),cosr(a,8)); }
    { int a0=2*c*g,a1=(2*c+1)*g; t.p2c[(32+l)*4]=pk(cosr(a0,8),cosr(a1,8)); t.p2c[(32+l)*4+1]=pk(sinr(a0,8),sinr(a1,8)); t.p2c[(32+l)*4+2]=pk(-sinr(a0,8),-sinr(a1,8)); t.p2c[(32+l)*4+3]=pk(cosr(a0,8),cosr(a1,8)); }
    for(int h=0;h<2;h++){ int a0=(8*h+2*c)*(2*g+1), a1=(8*h+2*c+1)*(2*g+1);
      t.p2c[(64+l)*4+h]=pk(cosr(a0,32),cosr(a1,32)); t.p2c[(64+l)*4+2+h]=pk(sinr(a0,32),sinr(a1,32));
      int b=8*h+g, b0=b*(4*c+1), b1=b*(4*c+3); t.p2c[(96+l)*4+2*h]=pk(cosr(b0,32),cosr(b1,32)); t.p2c[(96+l)*4+2*h+1]=pk(sinr(b0,32),sinr(b1,32)); }
    for(int u=0;u<4;u++){ int b=8*(u>>1)+2*c+(u&1), n=-b*(g+4); t.tw2[l*4+u]=(float)cosr(n,128); t.tw2[(32+l)*4+u]=(float)sinr(n,128); }
    for(int nt=0;nt<2;nt++){ int d1=4*nt+(g>>1); uint32_t v=d1<7?pk(cosr(d1*c,7),-sinr(d1*c,7)):0u; t.b7[4*l+2*nt]=(g&1)?0u:v; t.b7[4*l+2*nt+1]=(g&1)?v:0u; }
    for(int ty=0;ty<2;ty++){ for(int q=0;q<4;q++){ t.bandt[((ty*2+0)*32+l)*4+q]=band(8*q+2*c,g,ty?13:11,ty?19:13); t.bandt[((ty*2+1)*32+l)*4+q]=band(8*q+2*c,g,ty?4:6,ty?12:10); }
      int lo=ty?4:6; t.corr[(ty*32+l)*2]=band(2*c,g,lo,lo+1); t.corr[(ty*32+l)*2+1]=band(8+2*c,g,lo,lo+1); }
  }
  const double scale=2.0/(2048.0*448.0);
  for(int w=0;w<16;w++) for(int g=0;g<8;g++) for(int f=0;f<2;f++){ int d2=16*(w&3)+g+8*f, n=d2*(2*(w>>2)+7); t.tw3[(w*8+g)*4+2*f]=(float)(scale*cosr(n,896)); t.tw3[(w*8+g)*4+2*f+1]=(float)(scale*sinr(n,896)); }
  for(int e=0;e<512;e++){ int X=e+2; int a=(X<=512)?rbf(X):513, b=rbf(X-1); t.pwmap[e]=(uint32_t)(2*(a+1))|((uint32_t)(2*(b+1))<<16); }
  return t;
}
}
__device__ const __align__(128) ct::Tab g_tab = ct::make();
constexpr int CT_M64=0, CT_A7=8192, CT_TW1=8704, CT_P2C=12800, CT_TW2=14848, CT_TW3=15872, CT_B7=17920, CT_BAND=18432, CT_CORR=20480, CT_PWMAP=20992, CT_BYTES=23040;
static_assert(sizeof(ct::Tab)==CT_BYTES,"tab");

constexpr int SM_CT = 0;
constexpr int SM_B16F = 23040;
constexpr int SM_B16I = 24064;
constexpr int SM_MISC = 25088;
constexpr int SM_MB = SM_MISC+192;
constexpr int WS_P = 516;
constexpr int SM_WS = 25344;
constexpr int UC_PITCH = 656, UC_BYTES = 5248;
constexpr int SM_UC = 41984;
constexpr int TS_CLS = 4128;
constexpr int SM_TS = 62976;
constexpr int SM_XS = 79616;
constexpr int SM_YS = 93952;
constexpr int SM_BIG = 110976;
constexpr int SEED_WARP = 6656;
constexpr int CH_AREA = 28160;
constexpr int SM_GW = SM_BIG + 4*CH_AREA;
constexpr int SM_TOTAL = SM_GW + 896;
constexpr int PW0 = 64;
constexpr int OFF_PW = 3200;
constexpr int OFF_R4 = 5760, OFF_R8 = 6144, OFF_KC = 6528;
constexpr int OFF_KL = 17280;
constexpr int Z2P = 196*4, Z3P = 68*4;
constexpr int OFF_Z2 = 6656;
constexpr int OFF_Z3 = 12928;
constexpr int OFF_YF = 17280;
constexpr int OFF_Y3 = 23808;
constexpr int YS_KC = 528, YS_CLS = 8*528+32;
constexpr int SM_XB = SM_TS;
constexpr int YT_S = 66*4;
constexpr int SM_YB = SM_YS;
enum { MB_CT=0, MB_W=8, MB_XB=16, MB_TU=24, MB_YB=32, MB_T2=40, MB_U=48 };

__device__ uint32_t g_T[16*8*4*128*8];
__device__ uint32_t g_T2[128*16*4*32*2];
__device__ uint4    g_yb[128*896];
__device__ uint4    g_xT[448*256];
__device__ __align__(128) unsigned g_sync[32];
#define STAMP(i)

struct Params {
  const __nv_bfloat16 *x; const uint16_t *wr, *wi;
  const uint32_t *Are,*Aim,*Bre,*Bim,*Cre,*Cim;
  const __nv_bfloat16* logdt;
  const uint16_t *dskip;
  const uint4* gatew;
  uint4* out;
  uint32_t *T, *T2; uint4 *yb, *xT; unsigned* sync; const void* tab;
  uint32_t id;
};
enum { BAR_C=1, BAR_CH=2, BAR_S1=8, BAR_S2=9, BAR_S3=10, BAR_SX=11 };
constexpr int NB_CTA = 112;
constexpr int SPIN_MAX = 1<<16;

DEVI void spin_ge(const unsigned* p, unsigned target){
  unsigned v; int it=0;
  do{ asm volatile("ld.acquire.gpu.global.u32 %0,[%1];" : "=r"(v) : "l"(p) : "memory"); }while((int)(v-target)<0 && ++it<SPIN_MAX);
  asm volatile("fence.proxy.async.global;" ::: "memory");
}
DEVI void signal(unsigned* p){
  asm volatile("fence.acq_rel.gpu;" ::: "memory");
  asm volatile("red.relaxed.gpu.global.add.u32 [%0],1;" :: "l"(p) : "memory");
}
DEVI void kgen(uint32_t area, uint32_t sscale, int wid, int lane, float dt,
               uint32_t Are, uint32_t Aim, uint32_t Bre, uint32_t Bim, uint32_t Cre, uint32_t Cim){
  const int g=lane>>2, c=lane&3;
  float L[2],ph[2],cbr[2],cbi[2];
  const float dtl=dt*1.4426950408889634f;
#pragma unroll
  for(int m=0;m<2;m++){
    float bre=dt*(m?bf_hi(Bre):bf_lo(Bre)), bim=dt*(m?bf_hi(Bim):bf_lo(Bim));
    float cre=m?bf_hi(Cre):bf_lo(Cre), cim=m?bf_hi(Cim):bf_lo(Cim);
    L[m]=dtl*(m?bf_hi(Are):bf_lo(Are)); ph[m]=dt*(m?bf_hi(Aim):bf_lo(Aim));
    cbr[m]=fmaf(cre,bre,-(cim*bim)); cbi[m]=fmaf(cre,bim,cim*bre);
  }
  float mx=fmaxf(fmaxf(fabsf(cbr[0]),fabsf(cbi[0])),fmaxf(fabsf(cbr[1]),fabsf(cbi[1])));
  uint32_t eb=min(max(__reduce_max_sync(0xffffffffu,__float_as_uint(mx))>>23,2u),252u);
  const float dn=__uint_as_float((253u-eb)<<23);
  cbr[0]*=dn; cbr[1]*=dn; cbi[0]*=dn; cbi[1]*=dn;
  const int k0i=__reduce_add_sync(0xffffffffu,__float2int_rn((cbr[0]+cbr[1])*4194304.f));
  float pr[2],pi[2];
  C2 e1,e2,e4,e8,e16,e16c,e32c,e64c,e128c,e512,e1024,cb;
  cb.r=pack_f16(cbr[0],cbr[1]); cb.i=pack_f16(cbi[0],cbi[1]);
#define PK(dst) { dst.r=pack_f16(pr[0],pr[1]); dst.i=pack_f16(pi[0],pi[1]); }
#define PKC(dst) { dst.r=pack_f16(pr[0],pr[1]); dst.i=pack_f16(-pi[0],-pi[1]); }
#define SQ() { _Pragma("unroll") for(int m=0;m<2;m++){ float t=pr[m]*pi[m]; pr[m]=fmaf(pr[m],pr[m],-(pi[m]*pi[m])); pi[m]=t+t; } }
#define EXPN(n) { _Pragma("unroll") for(int m=0;m<2;m++){ float mag=ex2f(L[m]*(n)), a=ph[m]*(n); pr[m]=mag*cosaf(a); pi[m]=mag*sinaf(a); } }
  EXPN(1.0f); PK(e1); SQ(); PK(e2); SQ(); PK(e4); SQ(); PK(e8);
  EXPN(16.0f); PKC(e16c); e16.r=e16c.r; e16.i=e16c.i^0x80008000u;
  SQ(); PKC(e32c); SQ(); PKC(e64c); SQ(); PKC(e128c); SQ(); SQ(); PK(e512); SQ(); PK(e1024);
#undef PK
#undef PKC
#undef SQ
#undef EXPN
  const uint32_t wb = area + wid*SEED_WARP;
  {
    const uint32_t sA = wb + lane*128 + ((2*(lane&3)+((lane>>2)&1))<<4);
    C2 one; one.r=0x3c003c00u; one.i=0u;
    C2 G3=cmul2(e16c,e32c);
    C2 F0=cmul2(cb,e1), F1=cmul2(cb,e2), F2=cmul2(F1,e1);
    auto put=[&](int q, C2 G, C2 F){ sts128(sA^(q<<4),G.r,G.i,F.r,F.i); };
    put(0,one,F0); put(1,e16c,F1); put(2,e32c,F2); put(3,G3,cmul2(cb,e4));
    put(4,e64c,cmul2(F0,e4)); put(5,cmul2(e64c,e16c),cmul2(F1,e4)); put(6,cmul2(e64c,e32c),cmul2(F2,e4)); put(7,cmul2(e64c,G3),cmul2(cb,e8));
    const uint32_t sF = wb + 4096 + lane*64 + ((2*((lane>>1)&1)+((lane>>2)&1))<<4);
    C2 f=cmul2(cb,e512), k=cmul2(cb,e1024);
    C2 a0=cmul2(f,e4), a1=cmul2(f,e8), a2=cmul2(a0,e8), a3=cmul2(f,e16);
    sts128(sF,a0.r,a0.i,a1.r,a1.i); sts128(sF^16,a2.r,a2.i,a3.r,a3.i);
    C2 b0=cmul2(k,e8), b1=cmul2(k,e16), b2=cmul2(b0,e512), b3=cmul2(b1,e512);
    sts128(sF^32,b0.r,b0.i,b1.r,b1.i); sts128(sF^48,b2.r,b2.i,b3.r,b3.i);
    sts128(wb+6144+lane*16,e8.r,e8.i,e128c.r,e128c.i);
  }
  __syncwarp();
  float acc[6][4];
#pragma unroll
  for(int i=0;i<6;i++){ acc[i][0]=acc[i][1]=acc[i][2]=acc[i][3]=0.f; }
  {
    uint32_t pa=wb+c*128+((g^(2*c))<<4);
    uint32_t pf=wb+4096+c*64+(((g>>1)^(2*(c>>1)))<<4)+(g&1)*8;
    uint32_t pe=wb+6144+c*16;
#pragma unroll 1
    for(int s=0;s<4;s++){
#pragma unroll
      for(int h=0;h<2;h++){
        uint4 A=lds128(h?((pa^16)+512):pa);
        uint2 B=lds64(h?((pf^16)+256):pf);
        uint4 E=lds128(pe+h*64);
        C2 G0={A.x,A.y}, F0={A.z,A.w}, c8={E.x,E.y}, c128={E.z,E.w};
        C2 G1=cmul2(G0,c128), F1=cmul2(F0,c8), G2=cmul2(G1,c128), G3=cmul2(G2,c128);
        mma_f16(acc[0],G0.r,G1.r,G0.i,G1.i,F0.r,F0.i);
        mma_f16(acc[1],G0.r,G1.r,G0.i,G1.i,F1.r,F1.i);
        mma_f16(acc[2],G0.r,G1.r,G0.i,G1.i,B.x,B.y);
        mma_f16(acc[3],G2.r,G3.r,G2.i,G3.i,F0.r,F0.i);
        mma_f16(acc[4],G2.r,G3.r,G2.i,G3.i,F1.r,F1.i);
        mma_f16(acc[5],G2.r,G3.r,G2.i,G3.i,B.x,B.y);
      }
      pa+=1024; pf+=512; pe+=128;
    }
  }
  __syncwarp();
  const uint32_t sp = wb + lane*4;
#pragma unroll
  for(int i=0;i<6;i++){ sts32(sp+(2*i)*128,pack_f16(acc[i][0],acc[i][1])); sts32(sp+(2*i+1)*128,pack_f16(acc[i][2],acc[i][3])); }
  if(lane==0){ stsf(wb+24*128,(float)k0i*(1.0f/4194304.f)); sts32(sscale+wid*4,(eb+1)<<23); }
}

DEVI float2 h2f(uint32_t h){ float2 r; asm("{ .reg .b16 l,hh; mov.b32 {l,hh},%2; cvt.f32.f16 %0,l; cvt.f32.f16 %1,hh; }" : "=f"(r.x),"=f"(r.y) : "r"(h)); return r; }
DEVI void kreduce(uint32_t area, uint32_t sscale, int w, int lane){
  const int g=lane>>2, c=lane&3, mt=w>>1;
  const uint4 sc4=lds128(sscale);
  const uint32_t smax=max(max(sc4.x,sc4.y),max(sc4.z,sc4.w));
  auto rel=[&](uint32_t s){ const int de=(int)((smax-s)>>23); const uint32_t h=(de<=14)?(uint32_t)((15-de)<<10):0u; return h|(h<<16); };
  const uint32_t r0=rel(sc4.x), r1=rel(sc4.y), r2=rel(sc4.z), r3=rel(sc4.w);
  const float S=__uint_as_float(smax);
  auto red=[&](uint32_t a){ uint32_t v=h2mul(lds32(a),r0); v=h2fma(lds32(a+SEED_WARP),r1,v); v=h2fma(lds32(a+2*SEED_WARP),r2,v); v=h2fma(lds32(a+3*SEED_WARP),r3,v); float2 f=h2f(v); f.x*=S; f.y*=S; return f; };
  const uint32_t pn=area+lane*4+((mt*3+(w&1))*2)*128, pf=area+lane*4+((mt*3+2)*2+(w&1))*128;
  const float2 n0=red(pn), n1=red(pn+128), f0=red(pf);
  const uint32_t kl=area+OFF_KL+(8*(16*mt+g)+1+4*(w&1)+c)*4;
  sts32(kl,pack_bf16(n0.x,n0.y)); sts32(kl+256,pack_bf16(n1.x,n1.y));
  const int m=16*mt+g+8*(w&1);
  sts32(area+((c<2)?(OFF_R4+(16+c+2*m)*4):(OFF_R8+(16+m+32*(c-2))*4)), pack_bf16(f0.x,f0.y));
  if(w==3 && g==7){ if(c==3) stsf(area+OFF_KC,n1.y); if(c==1) stsf(area+OFF_KC+4,f0.y); }
  if(w==0 && lane==0){
    const float k0=__uint_as_float(sc4.x)*ldsf(area+24*128)+__uint_as_float(sc4.y)*ldsf(area+24*128+SEED_WARP)+__uint_as_float(sc4.z)*ldsf(area+24*128+2*SEED_WARP)+__uint_as_float(sc4.w)*ldsf(area+24*128+3*SEED_WARP);
    sts32(area+OFF_KL,pack_bf16(0.f,k0)); sts32(area+OFF_KL+257*4,0u); }
}
DEVI void kbuild(uint32_t area, uint32_t spwmap, int tid){
  const uint32_t kl=area+OFF_KL;
#pragma unroll
  for(int it=0;it<4;it++){
    const uint32_t mp=lds32(spwmap+(tid+128*it)*4);
    sts32(area+OFF_PW+(PW0+2+tid+128*it)*4, lds16(kl+(mp&0xffffu))|(lds16(kl+(mp>>16))<<16));
  }
  if(tid<2) sts32(area+OFF_PW+(PW0+tid)*4, lds16(kl+2*tid+2)|(lds16(kl+2*tid)<<16));
  if(tid<64){ sts32(area+OFF_PW+tid*4,0u); sts32(area+OFF_R4+(((tid>>4)&1)*80+(tid&15)+(tid>>5)*96)*4,0u); }
  else if(tid<126) sts32(area+OFF_PW+(514+tid)*4,0u);
}

DEVI void nearconv(uint32_t uc, uint32_t area, int w, int lane, float (&acc)[16], uint32_t id){
  const int g=lane>>2, c=lane&3;
  uint32_t pq=area+OFF_PW+(PW0+16*w+g-2*c-48)*4;
  uint64_t desc=make_desc(uc+9*16,UC_PITCH,128);
  uint32_t qa[4][4], qb[4][4];
  uint32_t prev=lds32(pq-32);
  auto load=[&](uint32_t (&q)[4][4]){
#pragma unroll
    for(int r=0;r<4;r++){ uint32_t x0=lds32(pq+(2*r)*32), x1=lds32(pq+(2*r+1)*32); q[r][0]=x0; q[r][1]=x1; q[r][2]=opq(prev,id); q[r][3]=opq(x0,id); prev=x1; }
    pq+=256;
  };
  auto issue=[&](uint32_t (&q)[4][4]){
    wg_fence();
#pragma unroll
    for(int r=0;r<4;r++) wgmma_rs_n32(acc,q[r][0],q[r][1],q[r][2],q[r][3],desc+(uint64_t)((2*(3-r)*UC_PITCH)>>4));
    wg_commit();
    desc-=1;
  };
  load(qa);
#pragma unroll 1
  for(int u=0;u<4;u++){
    issue(qa);
    wg_wait<1>();
    load(qb);
    issue(qb);
    wg_wait<1>();
    load(qa);
  }
  issue(qa);
  wg_wait<0>();
}
DEVI uint32_t uc_row(uint32_t uc, int m){ return uc + (m&7)*UC_PITCH + ((m>>3)+9)*16; }

DEVI void win_pair(uint32_t a0p, uint32_t a1p, uint32_t da, uint4 ba, uint4 bb, uint32_t dst, uint32_t zp){
  uint32_t a[2][8];
#pragma unroll
  for(int q=0;q<2;q++){ ldsm_x4(a[q][0],a[q][1],a[q][2],a[q][3],a0p+q*da); ldsm_x4(a[q][4],a[q][5],a[q][6],a[q][7],a1p+q*da); }
#pragma unroll
  for(int q=0;q<2;q++){
    float wa[4], wb[4];
    mma_bf16z(wa,a[q][0],a[q][1],a[q][2],a[q][3],ba.x,ba.y); mma_bf16z(wb,a[q][0],a[q][1],a[q][2],a[q][3],bb.x,bb.y);
    mma_bf16(wa,a[q][4],a[q][5],a[q][6],a[q][7],ba.z,ba.w); mma_bf16(wb,a[q][4],a[q][5],a[q][6],a[q][7],bb.z,bb.w);
    sts32(dst+q*64,pack_bf16(wa[0],wb[0])); sts32(dst+q*64+zp,pack_bf16(wa[1],wb[1]));
    sts32(dst+q*64+32,pack_bf16(wa[2],wb[2])); sts32(dst+q*64+zp+32,pack_bf16(wa[3],wb[3]));
  }
}
DEVI void far_group(uint32_t ca, uint32_t dca, uint32_t za, bool skip8, const uint32_t (&qd)[10][4], float kc, uint32_t cb0, uint32_t cb1,
                    uint32_t dst, uint32_t dj, uint32_t dh){
  float acc[4][4], acc2[4][4];
#pragma unroll
  for(int j=0;j<4;j++){
    uint32_t a0,a1,a2,a3; ldsm_x4(a0,a1,a2,a3,ca+j*dca);
    mma_bf16z(acc2[j],a0,a1,a2,a3,cb0,cb1);
    acc2[j][0]*=kc; acc2[j][1]*=kc; acc2[j][2]*=kc; acc2[j][3]*=kc;
    acc[j][0]=acc[j][1]=acc[j][2]=acc[j][3]=0.f;
  }
#pragma unroll
  for(int half=0;half<2;half++){
    if(half==1 || !skip8){
#pragma unroll
      for(int tau=8*half;tau<8*half+8;tau+=2){
        uint32_t b0,b1,b2,b3; ldsm_x4(b0,b1,b2,b3,za+tau*32);
#pragma unroll
        for(int j=0;j<4;j++){
          const int t=tau-2*j;
          if(t>=0 && t<10){
            mma_bf16(acc[j],qd[t][0],qd[t][1],qd[t][2],qd[t][3],b0,b1);
            mma_bf16(acc2[j],qd[t+1][0],qd[t+1][1],qd[t+1][2],qd[t+1][3],b2,b3);
          }
        }
      }
    }
  }
#pragma unroll
  for(int j=0;j<4;j++){ sts64f(dst+j*dj,acc[j][0]+acc2[j][0],acc[j][1]+acc2[j][1]); sts64f(dst+j*dj+dh,acc[j][2]+acc2[j][2],acc[j][3]+acc2[j][3]); }
}
DEVI void load_quads(uint32_t rb, uint32_t (&qd)[10][4], uint32_t id){
#pragma unroll
  for(int t=0;t<10;t++){
    qd[t][0]=lds32(rb+(32-2*t)*16); qd[t][2]=lds32(rb+(31-2*t)*16);
    if(t==0){ qd[t][1]=lds32(rb+34*16); qd[t][3]=lds32(rb+33*16); }
    else { qd[t][1]=opq(qd[t-1][0],id); qd[t][3]=opq(qd[t-1][2],id); }
  }
}

DEVI void p2_job(const uint4& F8, const uint4& F8i, const uint4& Bcs, const uint4& Ic, const float (&tr)[4], const float (&ti)[4], const uint32_t (&wrow)[4],
                 uint32_t sb, int cls, int jj, int lane){
  const int g=lane>>2;
  const uint32_t tb=sb+SM_TS+cls*TS_CLS+lane*32;
  uint2 wv[4];
#pragma unroll
  for(int u=0;u<4;u++) wv[u]=lds64(tb+u*1024+((jj^((g^(2*u+(g>>2)))&3))<<3));
  uint32_t outw[2][4];
#pragma unroll
  for(int mir=0;mir<2;mir++){
    const uint32_t wo=sb+SM_WS+(cls*8+jj*2+mir)*WS_P;
    float D1[2][4];
#pragma unroll
    for(int h=0;h<2;h++) mma_bf16z(D1[h],F8.x,F8.y,F8.z,F8.w, mir?wv[2*h].y:wv[2*h].x, mir?wv[2*h+1].y:wv[2*h+1].x);
    uint32_t ww[4];
#pragma unroll
    for(int u=0;u<4;u++) ww[u]=lds32(wo+wrow[u]);
    float yr[4],yi[4];
#pragma unroll
    for(int u=0;u<4;u++){ float a=D1[u>>1][u&1], b=D1[u>>1][2+(u&1)]; yr[u]=fmaf(a,tr[u],-(b*ti[u])); yi[u]=fmaf(a,ti[u],b*tr[u]); }
    float PR[4], TQ[4];
    { uint32_t a0=pack_bf16(yr[0],yr[1]), a1=pack_bf16(yi[0],yi[1]), a2=pack_bf16(yr[2],yr[3]), a3=pack_bf16(yi[2],yi[3]);
      mma_bf16z(PR,a0,a1,a2,a3,Bcs.x,Bcs.y); mma_bf16z(TQ,a0,a1,a2,a3,Bcs.z,Bcs.w); }
    float Er[2],Ei[2],Or[2],Oi[2];
#pragma unroll
    for(int e=0;e<2;e++){
      float P=PR[e],R=PR[2+e],T=TQ[e],Q=TQ[2+e];
      float x1r=P+Q,x1i=R-T,x2r=P-Q,x2i=R+T;
      float w1r=bf_lo(ww[2*e]), w1i=bf_hi(ww[2*e]), w2r=bf_lo(ww[2*e+1]), w2i=bf_hi(ww[2*e+1]);
      float z1r=fmaf(x1r,w1r,-(x1i*w1i)), z1i=fmaf(x1r,w1i,x1i*w1r), z2r=fmaf(x2r,w2r,-(x2i*w2i)), z2i=fmaf(x2r,w2i,x2i*w2r);
      Er[e]=z1r+z2r; Ei[e]=z1i+z2i; Or[e]=z1r-z2r; Oi[e]=z2i-z1i;
    }
    float H[2][4];
    { uint32_t a0=pack_bf16(Er[0],Er[1]), a1=pack_bf16(Ei[0],Ei[1]), a2=pack_bf16(Oi[0],Oi[1]), a3=pack_bf16(Or[0],Or[1]);
      mma_bf16z(H[0],a0,a1,a2,a3,Ic.x,Ic.y); mma_bf16z(H[1],a0,a1,a2,a3,Ic.z,Ic.w); }
#pragma unroll
    for(int h=0;h<2;h++){
      float hr[2],hi[2];
#pragma unroll
      for(int e=0;e<2;e++){ int u=2*h+e; float a=H[h][e], b=H[h][2+e]; hr[e]=fmaf(a,tr[u],b*ti[u]); hi[e]=fmaf(b,tr[u],-(a*ti[u])); }
      uint32_t mr=movm(pack_bf16(hr[0],hr[1])), mi=movm(pack_bf16(hi[0],hi[1]));
      float U[4]; mma_bf16z(U,F8i.x,F8i.y,F8i.z,F8i.w,mr,mi);
      outw[mir][2*h]=pack_bf16(U[0],U[2]); outw[mir][2*h+1]=pack_bf16(U[1],U[3]);
    }
  }
  const int cq=lane&3;
  const uint32_t so=sb+SM_TS+cls*TS_CLS+(16*g+2*cq)*32;
#pragma unroll
  for(int u=0;u<4;u++) sts64(so+(8*(u>>1)+(u&1))*32+((jj^(((2*(u>>1)+(cq>>1))^g)&3))<<3),outw[0][u],outw[1][u]);
}
__global__ void __launch_bounds__(640,1) fused_kernel(const Params p){
  extern __shared__ __align__(1024) unsigned char smem[];
  const uint32_t sb=smem_u32(smem);
  const int tid=threadIdx.x, lane=tid&31, g=lane>>2, c=lane&3;
  const int warp=__shfl_sync(0xffffffffu,tid>>5,0);
  const int cta=blockIdx.x;
  const bool hasB = cta<NB_CTA;
  const uint32_t mb=sb+SM_MB;
  STAMP(0);
  asm volatile("" :: "l"(p.x),"l"(p.Cim),"l"(p.out),"l"(p.xT),"l"(p.tab),"r"(p.id));
  if(warp>=16){
    unsigned ep=0;
    if(warp==16){
      if(lane==0){
        mbar_init(mb+MB_CT,1); mbar_init(mb+MB_TU,1); mbar_init(mb+MB_YB,1); mbar_init(mb+MB_T2,1); mbar_init(mb+MB_W,2); mbar_init(mb+MB_XB,512); mbar_init(mb+MB_U,1);
        asm volatile("fence.mbarrier_init.release.cluster;" ::: "memory");
        mbar_expect(mb+MB_CT,CT_BYTES-12800);
        bulk_g2s(sb+SM_CT+12800,(const char*)p.tab+12800,CT_BYTES-12800,mb+MB_CT);
      }
      if(lane==0){
      }
      __syncwarp();
    }
    if(lane==0) asm volatile("ld.relaxed.gpu.global.u32 %0,[%1];" : "=r"(ep) : "l"(&p.sync[0]) : "memory");
    bar_sync(0,640);
    if(warp>=18 && lane==0) asm volatile("cp.async.bulk.prefetch.L2.global [%0],%1;" :: "l"((warp==18?p.wr:p.wi)+(size_t)cta*3600),"r"(7200) : "memory");
    if(warp>=18){
      bar_sync(BAR_S1,608);
      const int b=warp-18, k1u=cta>>3, qu=cta&7, scl=lane>>3, sj=4*qu+((lane>>1)&3);
      int fn=(lane&1)? (sj==0?scl:7*sj-scl) : (scl+7*(sj+1)); if(fn>224) fn=448-fn;
#pragma unroll 1
      for(int h=0;h<2;h++){
        const int bb=2*b+h;
        const uint16_t* wr=p.wr+(k1u+512*bb)*225+fn; const uint16_t* wi=p.wi+(k1u+512*bb)*225+fn;
        const uint32_t wd=sb+SM_WS+lane*WS_P+128*bb;
        uint32_t vr[32],vi[32];
#pragma unroll
        for(int r=0;r<32;r++){ vr[r]=wr[r*3600]; vi[r]=wi[r*3600]; }
#pragma unroll
        for(int r=0;r<32;r++) sts32(wd+(r^((bb&1)<<3))*4, vr[r]|(vi[r]<<16));
      }
      __syncwarp();
      if(lane==0) mbar_arrive(mb+MB_W);
      {
        const uint4 gw0=lds128(sb+SM_GW+lane*16), gw1=lds128(sb+SM_GW+min(32+lane,55)*16);
#pragma unroll 2
        for(int rr=0;rr<8;rr++){
          const int row=8*(warp-18)+rr;
          const uint32_t xd=sb+SM_XS+row*896+(lane>>3)*128;
          uint4 v=lds128(xd+(((lane&7)^(lane>>3))<<4));
          uint32_t a=bmul(v.x,gw0.x), b=bmul(v.y,gw0.y), cc=bmul(v.z,gw0.z), d=bmul(v.w,gw0.w);
          float acc=(bf_lo(a)+bf_hi(a))+(bf_lo(b)+bf_hi(b))+(bf_lo(cc)+bf_hi(cc))+(bf_lo(d)+bf_hi(d));
          if(lane<24){ v=lds128(xd+512+(((lane&7)^(4+(lane>>3)))<<4));
            a=bmul(v.x,gw1.x); b=bmul(v.y,gw1.y); cc=bmul(v.z,gw1.z); d=bmul(v.w,gw1.w);
            acc+=(bf_lo(a)+bf_hi(a))+(bf_lo(b)+bf_hi(b))+(bf_lo(cc)+bf_hi(cc))+(bf_lo(d)+bf_hi(d)); }
#pragma unroll
          for(int o=16;o;o>>=1) acc+=__shfl_xor_sync(0xffffffffu,acc,o);
          const float sv=__bfloat162float(__float2bfloat16(acc)); const float gg=__bfloat162float(__float2bfloat16(__fdividef(1.0f,1.0f+__expf(-sv))));
          if(lane==0){ sts32(sb+SM_MISC+64+row*4,pack_bf16(gg,gg)); sts32(sb+SM_MISC+128+row*4,pack_bf16(1.0f-gg,1.0f-gg)); }
        }
      }
      bar_arrive(15,64+64);
    }
    ep+=1;
    if(warp==16){
      bar_sync(BAR_S1,608);
      if(lane==0) signal(&p.sync[1]);
      bar_sync(BAR_SX,544);
      if(lane==0){
        spin_ge(&p.sync[1],ep*128u);
        sts32(sb+SM_MISC+252,ep&1u);
        mbar_expect(mb+MB_TU,16384);
        for(int k=0;k<4;k++) bulk_g2s(sb+SM_TS+k*TS_CLS, p.T+(size_t)cta*4096+k*1024, 4096, mb+MB_TU);
      }
      STAMP(1);
      bar_sync(15,64+64);
      if(lane==0){ signal(&p.sync[2]); spin_ge(&p.sync[2],ep*128u); mbar_expect(mb+MB_T2,16384); bulk_g2s(sb+SM_TS,p.T2+(size_t)cta*4096,16384,mb+MB_T2); }
      STAMP(2);
      if(hasB) bar_sync(BAR_S3,544);
      if(lane==0){
        if(hasB) asm volatile("red.relaxed.gpu.global.add.u32 [%0],1;" :: "l"(&p.sync[3]) : "memory");
        unsigned v; int it=0; const unsigned target=ep*(unsigned)NB_CTA;
        do{ asm volatile("ld.relaxed.gpu.global.u32 %0,[%1];" : "=r"(v) : "l"(&p.sync[3]) : "memory"); }while((int)(v-target)<0 && ++it<SPIN_MAX);
        mbar_arrive(mb+MB_YB);
        if(cta==0) p.sync[0]=ep;
      }
      STAMP(4);
    } else if(warp==17){
      bar_sync(14,544);
      if(lane==0){
        signal(&p.sync[4]);
        if(hasB){ spin_ge(&p.sync[4],ep*128u); mbar_expect(mb+MB_U,16384); }
      }
      __syncwarp();
      if(hasB){ asm volatile("fence.proxy.async.global;" ::: "memory"); bulk_g2s(sb+SM_UC+(lane>>3)*UC_BYTES+(lane&7)*UC_PITCH+144, p.xT+(size_t)(4*cta+(lane>>3))*256+(lane&7)*32, 512, mb+MB_U); }
      bar_sync(BAR_S2,544);
      {
        const int k1u=cta>>3, qu=cta&7, cl=(lane>>1)&3, hf=lane&1;
        const uint32_t so=sb+SM_TS+cl*TS_CLS+(lane>>3)*32+hf*16;
        uint4* dst=(uint4*)p.T2+(((lane>>3)*16+k1u)*8+qu)*8+((cl^((k1u>>1)&3))<<1)+hf;
#pragma unroll 16
        for(int i=0;i<32;i++) dst[i*4*1024]=lds128(so+i*128);
      }
      bar_arrive(15,64+64);
    }
    return;
  }
  const int wg=warp>>2, w=warp&3;
  const int s2=cta;
  {
    const __nv_bfloat16* xr=p.x+(size_t)(128*warp+s2)*448+lane*8;
    const uint32_t xd=sb+SM_XS+warp*896+(lane>>3)*128;
    cp_async16(xd+(((lane&7)^(lane>>3))<<4), xr);
    if(lane<24) cp_async16(xd+512+(((lane&7)^(4+(lane>>3)))<<4), xr+256);
    cp_async16(sb+SM_CT+tid*16,(const uint4*)p.tab+tid);
    if(tid<288) cp_async16(sb+SM_CT+8192+tid*16,(const uint4*)p.tab+512+tid);
    if(tid<56) cp_async16(sb+SM_GW+tid*16, p.gatew+tid);
    cp_commit();
  }
  if(hasB){
    const int xtb=cta/7, xcb=cta-7*xtb;
#pragma unroll
    for(int ps=0;ps<2;ps++){ const int t=8*warp+4*ps+(lane>>3);
      cp_async16(sb+SM_XB+t*128+(((lane&7)^((t&1)|((t>>2)&2)|((t>>4)&4)))<<4), p.x+(size_t)(128*xtb+t)*448+64*xcb+(lane&7)*8); }
  }
  uint32_t rAre=0,rAim=0,rBre=0,rBim=0,rCre=0,rCim=0, rldt=0;
  if(hasB){ const int dch=4*cta+wg, pi=dch*128+w*32+lane; rAre=p.Are[pi]; rAim=p.Aim[pi]; rBre=p.Bre[pi]; rBim=p.Bim[pi]; rCre=p.Cre[pi]; rCim=p.Cim[pi]; rldt=((const uint16_t*)p.logdt)[dch]; }
  { const bool inv=tid>=256; const int t=tid&255, kc=t>>7, n=(t>>2)&31, pp=t&3, k=8*kc+2*pp, nn=n&15;
    const int m0=inv? ((128*nn+s2)*k):((128*k+s2)*nn), m1=m0+(inv?(128*nn+s2):128*nn);
    float a0=(float)(m0&2047)*(PI2/2048.f), a1=(float)(m1&2047)*(PI2/2048.f);
    if(n<16){ a0=cosaf(a0); a1=cosaf(a1); } else { a0=sinaf(a0); a1=sinaf(a1); if(!inv){ a0=-a0; a1=-a1; } }
    sts32(sb+SM_B16F+(inv?1024:0)+kc*512+n*16+pp*4, pack_bf16(a0,a1)); }
  if(hasB && tid<288){ const int v=tid/72, r=tid-72*v, kc=r/9; sts128(sb+SM_UC+v*UC_BYTES+kc*UC_PITCH+(r-9*kc)*16,0,0,0,0); }
  cp_wait<0>();
  STAMP(1);
  bar_sync(0,640);
  cp_mbar_arrive(mb+MB_XB);
  STAMP(2);
  {
    const uint4 A7=lds128(sb+CT_A7+lane*16);
    const int J=warp&7, d1=min(lane&7,6);
    const uint4 tw=lds128(sb+CT_TW1+(J*32+lane)*16);
    const float twr0=__uint_as_float(tw.x), twi0=__uint_as_float(tw.y), twr1=__uint_as_float(tw.z), twi1=__uint_as_float(tw.w);
    const uint32_t src=sb+SM_XS+(8*(warp>>3)+(lane>>3))*896+d1*128+((J^d1)<<4);
    const uint32_t dst=sb+SM_YS+(g&3)*YS_CLS+J*YS_KC+(8*(warp>>3)+(g>>2))*16+4*c;
#pragma unroll
    for(int ii=0;ii<2;ii++){
      uint32_t b0,b1,b2,b3;
      ldsm_x4t(b0,b1,b2,b3,src+ii*4*896);
#pragma unroll
      for(int h=0;h<2;h++){
        float a[4]; mma_bf16z(a,A7.x,A7.y,A7.z,A7.w,h?b2:b0,h?b3:b1);
        sts32(dst+(4*ii+2*h)*16,     pack_bf16(fmaf(a[0],twr0,-(a[2]*twi0)), fmaf(a[1],twr1,-(a[3]*twi1))));
        sts32(dst+(4*ii+2*h)*16+256, pack_bf16(fmaf(a[0],twi0,a[2]*twr0),    fmaf(a[1],twi1,a[3]*twr1)));
      }
    }
  }
  fence_async();
  bar_sync(BAR_C,512);
  STAMP(15);
  const int jrow=8*w+g;
  {
    float d[16];
    const uint64_t da=make_desc(sb+CT_M64,1024,128), db=make_desc(sb+SM_YS+wg*YS_CLS,YS_KC,128);
    wg_fence();
#pragma unroll
    for(int ks=0;ks<4;ks++) wgmma_ss_n32<0,0>(d,da+(uint64_t)((2*ks*1024)>>4),db+(uint64_t)((2*ks*YS_KC)>>4),ks);
    wg_commit();
    wg_wait<0>();
    const uint32_t md=(wg!=0 && jrow==31)?0x80008000u:0u, mm=(jrow!=0)?0x80008000u:0u;
    uint32_t Ad[4],Am[4];
#pragma unroll
    for(int t=0;t<2;t++){
      float dr[2],di[2],mr[2],mi_[2];
#pragma unroll
      for(int e=0;e<2;e++){ const float P=d[4*t+e],T=d[4*t+2+e],R=d[4*(t+2)+e],Q=d[4*(t+2)+2+e]; dr[e]=P+Q; di[e]=R-T; mr[e]=P-Q; mi_[e]=R+T; }
      Ad[2*t]=pack_bf16(dr[0],dr[1]); Ad[2*t+1]=pack_bf16(di[0],di[1])^md;
      Am[2*t]=pack_bf16(mr[0],mr[1]); Am[2*t+1]=pack_bf16(mi_[0],mi_[1])^mm;
    }
    float od[16],om[16];
    const uint64_t db16=make_desc(sb+SM_B16F,512,128);
    wg_fence();
    wgmma_rs_n32z(od,Ad[0],Ad[1],Ad[2],Ad[3],db16);
    wgmma_rs_n32z(om,Am[0],Am[1],Am[2],Am[3],db16);
    wg_commit(); wg_wait<0>();
    const int pos=(((s2>>6)&1)+2*((s2>>3)&1))*32+4*(s2&7)+((s2>>4)&3);
    uint32_t* dst=p.T+(((((2*c)*8+(jrow>>2))*4+wg)*128+pos)*4+((jrow&3)^(((pos>>2)^(pos>>4))&3)))*2;
#pragma unroll
    for(int t=0;t<2;t++)
#pragma unroll
      for(int e=0;e<2;e++){
        const uint32_t wd=pack_bf16(od[4*t+e]-od[4*(t+2)+2+e], od[4*(t+2)+e]+od[4*t+2+e]);
        const uint32_t wm=pack_bf16(om[4*t+e]-om[4*(t+2)+2+e], om[4*(t+2)+e]+om[4*t+2+e]);
        *(uint2*)(dst+(8*t+e)*32768)=make_uint2(wd,wm);
      }
  }
  bar_arrive(BAR_S1,608);
  if(wg>=2) mbar_wait(mb+MB_XB);
  {
    if(hasB && wg>=2){
      const int xtb=cta/7, xcb=cta-7*xtb;
#pragma unroll
      for(int it=0;it<4;it++){
        const int u=(warp-8)+8*it, ch=u>>2, kp=u&3, mi=lane>>3, r=lane&7, cc=r>>1;
        const int t=64*(cc&1)+16*kp+8*(cc>>1)+2*mi+(r&1);
        uint32_t v0,v1,v2,v3; ldsm_x4t(v0,v1,v2,v3,sb+SM_XB+t*128+((ch^((t&1)|((t>>2)&2)|((t>>4)&4)))<<4));
        p.xT[(64*xcb+8*ch+g)*256+(2*kp+(c>>1))*32+2*xtb+(c&1)]=make_uint4(v0,v1,v2,v3);
      }
    }
  }
  bar_arrive(BAR_SX,544);
  bar_arrive(14,544);
  STAMP(3);
  const uint32_t uc=sb+SM_UC+wg*UC_BYTES, ar=sb+SM_BIG+wg*CH_AREA;
  if(hasB){
    asm volatile("" : "+r"(rldt), "+r"(rAre), "+r"(rAim), "+r"(rBre), "+r"(rBim), "+r"(rCre), "+r"(rCim));
    const float dt=__bfloat162float(__float2bfloat16(expf(__uint_as_float(rldt<<16))));
    kgen(ar,sb+SM_MISC+wg*16,w,lane,dt,rAre,rAim,rBre,rBim,rCre,rCim);
  }
  mbar_wait(mb+MB_CT);
  if(hasB){
    bar_sync(BAR_CH+wg,128);
    STAMP(4);
    kreduce(ar,sb+SM_MISC+wg*16,w,lane);
    bar_sync(BAR_CH+wg,128);
    kbuild(ar,sb+CT_PWMAP,tid&127);
  }
  if(w==0){ mbar_wait(mb+MB_W); mbar_wait(mb+MB_TU); }
  bar_sync(BAR_CH+wg,128);
  STAMP(5);
  if(w<2 || !hasB){
    const uint4 F8=lds128(sb+CT_P2C+lane*16), F8i=lds128(sb+CT_P2C+512+lane*16), Bcs=lds128(sb+CT_P2C+1024+lane*16), Ic=lds128(sb+CT_P2C+1536+lane*16);
    const uint4 t0=lds128(sb+CT_TW2+lane*16), t1=lds128(sb+CT_TW2+512+lane*16);
    const float tr[4]={__uint_as_float(t0.x),__uint_as_float(t0.y),__uint_as_float(t0.z),__uint_as_float(t0.w)};
    const float ti[4]={__uint_as_float(t1.x),__uint_as_float(t1.y),__uint_as_float(t1.z),__uint_as_float(t1.w)};
    uint32_t wrow[4];
#pragma unroll
    for(int e=0;e<2;e++){ const int jb=2*c+e, r1=g+8*(jb+1), r2=g+8*((16-jb)&15); wrow[2*e]=(r1^((r1>>2)&8))*4; wrow[2*e+1]=(r2^((r2>>2)&8))*4; }
#pragma unroll 1
    for(int jj=w; jj<4; jj+=(hasB?2:4)) p2_job(F8,F8i,Bcs,Ic,tr,ti,wrow,sb,wg,jj,lane);
  }
  bar_arrive(BAR_S2,544);
  STAMP(6);
  if(hasB){
    const int arow=(lane&7)+8*((lane>>3)&1), akc=lane>>4;
    if(w>=2){
      mbar_wait(mb+MB_U);
      const int hw=w-2;
#pragma unroll 1
      for(int ty=0;ty<2;ty++){
        const uint4 ba=lds128(sb+CT_BAND+ty*1024+lane*16), bb=lds128(sb+CT_BAND+ty*1024+512+lane*16);
        const int m0 = ty? (2*arow+hw-3+akc) : (96*hw+arow-2+akc);
        const uint32_t a0=uc_row(uc,m0), a1=uc_row(uc,m0+2), da=ty?64:32, zp=ty?Z3P:Z2P;
        const uint32_t dst = ty? (ar+OFF_Z3+(8*hw+2*c)*Z3P+g*4) : (ar+OFF_Z2+(2*c)*Z2P+(96*hw+g)*4);
        const int np=ty?2:3;
#pragma unroll 1
        for(int q=0;q<np;q++) win_pair(a0+2*q*da,a1+2*q*da,da,ba,bb,dst+q*128,zp);
        if(ty==0) bar_arrive((wg<2)?6+wg:10+wg,128);
      }
      __syncwarp();
    } else {
      bar_sync((wg<2)?6+wg:10+wg,128);
    }
    STAMP(7);
    {
#pragma unroll 1
      for(int ph=0; ph<((w==2)?2:1); ph++){
        const bool f3=(w>=2) && ph==0;
        const int i0=(w>=2)?4:8+4*w, h=w-2;
        uint32_t qd[10][4];
        load_quads(ar+(f3?OFF_R8:OFF_R4)+(g-c-48)*4,qd,p.id);
        const float kc=ldsf(ar+OFF_KC+(f3?4:0));
        const uint2 cb=lds64(sb+CT_CORR+(f3?256:0)+lane*8);
        const uint32_t ca=uc_row(uc,f3?(2*arow+h-1+akc):(16*i0+arow-65+akc));
        const uint32_t za=f3?(ar+OFF_Z3+((lane&7)+8*h)*Z3P+(lane>>3)*16-8*32):(ar+OFF_Z2+(lane&7)*Z2P+(lane>>3)*16+(2*i0-16)*32);
        const uint32_t dst=f3?(ar+OFF_Y3+(16*g+8*h+2*c+4*(g>>2))*4):(ar+OFF_YF+(136*i0-544+8*g+2*c)*4);
        far_group(ca,f3?64:32,za,i0==4,qd,kc,cb.x,cb.y,dst,f3?(256+16)*4:(128+8)*4,f3?(128+8)*4:(64+4)*4);
      }
    }
    bar_sync(BAR_CH+wg,128);
    STAMP(8);
    float acc[16];
    {
      const uint32_t yf=ar+OFF_YF+(128*c+16*w+g-512+4*(2*c-8))*4;
      const uint32_t y3=ar+OFF_Y3+(128*c+16*w+g-1024+4*(2*c-16))*4;
#pragma unroll
      for(int J=0;J<4;J++)
#pragma unroll
        for(int f=0;f<2;f++)
#pragma unroll
          for(int e=0;e<2;e++){
            const int o=(512*J+64*e+8*f+4*(8*J+e))*4;
            float val=0.f;
            if(J>=1) val=ldsf(yf+o);
            if(J>=2) val+=ldsf(y3+o);
            acc[4*J+2*f+e]=val;
          }
    }
    nearconv(uc,ar,w,lane,acc,p.id);
    STAMP(9);
    {
      const int d=4*cta+wg;
      const uint32_t dsk=p.dskip[d]; const uint32_t DD=dsk|(dsk<<16);
      const uint32_t ux=uc+(2*w+((lane>>3)&1))*UC_PITCH+((lane>>4)*8+(lane&7)+9)*16;
      uint32_t xu[2][4];
      ldsm_x4t(xu[0][0],xu[1][0],xu[0][1],xu[1][1],ux);
      ldsm_x4t(xu[0][2],xu[1][2],xu[0][3],xu[1][3],ux+256);
      uint32_t bp[2][4];
#pragma unroll
      for(int f=0;f<2;f++)
#pragma unroll
        for(int J=0;J<4;J++) bp[f][J]=badd(pack_bf16(acc[4*J+2*f],acc[4*J+2*f+1]),bmul(xu[f][J],DD));
      uint4* dst=p.yb+(16*w+g+8*(c&1))*896+((2*d+(c>>1))^((((d>>6)&1)<<2)|((d>>7)&1)));
      const bool odd=c&1;
      const uint32_t tag=lds32(sb+SM_MISC+252);
#pragma unroll
      for(int e=0;e<2;e++){
        const uint32_t sel=e?0x7632u:0x5410u;
        const uint32_t w00=__byte_perm(bp[0][0],bp[0][1],sel), w01=__byte_perm(bp[0][2],bp[0][3],sel), w10=__byte_perm(bp[1][0],bp[1][1],sel), w11=__byte_perm(bp[1][2],bp[1][3],sel);
        const uint32_t r0=__shfl_xor_sync(0xffffffffu,odd?w00:w10,1), r1=__shfl_xor_sync(0xffffffffu,odd?w01:w11,1);
        st_rlx128(dst+(64*e)*896, ((odd?r0:w00)&~1u)|tag, odd?r1:w01, odd?w10:r0, odd?w11:r1);
      }
    }
  }
  if(hasB) bar_arrive(BAR_S3,544);
  STAMP(10);
  mbar_wait(mb+MB_T2);
  uint2 u[4];
  { const uint32_t src=sb+SM_TS+((2*c)*8+(jrow>>2))*128+((wg^c)<<5)+(((jrow&3)^(((s2>>2)^(s2>>4))&3))<<3);
#pragma unroll
    for(int t=0;t<4;t++) u[t]=lds64(src+(8*(t>>1)+(t&1))*1024); }
  {
    float od[16],om[16];
    const uint64_t db=make_desc(sb+SM_B16I,512,128);
    wg_fence();
    wgmma_rs_n32z(od,__byte_perm(u[0].x,u[1].x,0x5410),__byte_perm(u[0].x,u[1].x,0x7632),__byte_perm(u[2].x,u[3].x,0x5410),__byte_perm(u[2].x,u[3].x,0x7632),db);
    wgmma_rs_n32z(om,__byte_perm(u[0].y,u[1].y,0x5410),__byte_perm(u[0].y,u[1].y,0x7632),__byte_perm(u[2].y,u[3].y,0x5410),__byte_perm(u[2].y,u[3].y,0x7632),db);
    wg_commit(); wg_wait<0>();
    float wd=1.f, wm=1.f;
    if(wg==0){ wd=(jrow<=30)?1.f:0.5f; wm=(jrow==0)?0.5f:0.f; }
    const float sd=(wg!=0 && jrow==31)?-wd:wd, sm_=(jrow!=0)?-wm:wm;
    const uint32_t bp=ar+g*16+4*c+(2*w)*512;
#pragma unroll
    for(int t=0;t<2;t++){
      float Er[2],Ei[2],Or[2],Oi[2];
#pragma unroll
      for(int e=0;e<2;e++){
        const float dr=(od[4*t+e]-od[4*(t+2)+2+e])*wd, di=(od[4*(t+2)+e]+od[4*t+2+e])*sd;
        const float mr=(om[4*t+e]-om[4*(t+2)+2+e])*wm, mi_=(om[4*(t+2)+e]+om[4*t+2+e])*sm_;
        Er[e]=dr+mr; Ei[e]=di+mi_; Or[e]=dr-mr; Oi[e]=mi_-di;
      }
      sts32(bp+t*128,pack_bf16(Er[0],Er[1])); sts32(bp+(2+t)*128,pack_bf16(Ei[0],Ei[1]));
      sts32(bp+512+t*128,pack_bf16(Oi[0],Oi[1])); sts32(bp+512+(2+t)*128,pack_bf16(Or[0],Or[1]));
    }
  }
  fence_async();
  bar_sync(BAR_CH+wg,128);
  {
    float d[16];
    const uint64_t da=make_desc(sb+CT_M64,128,1024), db=make_desc(ar,512,128);
    wg_fence();
#pragma unroll
    for(int ks=0;ks<4;ks++) wgmma_ss_n32<1,1>(d,da+(uint64_t)((ks*256)>>4),db+(uint64_t)((ks*1024)>>4),ks);
    wg_commit();
    const uint4 tw=lds128(sb+CT_TW3+(warp*8+g)*16);
    wg_wait<0>();
    const uint32_t yt=ar+4096+wg*32+(8*(c&1)+(c>>1))*YT_S+(16*w+g)*4;
#pragma unroll
    for(int f=0;f<2;f++){
      const float cc=__uint_as_float(f?tw.z:tw.x), s=__uint_as_float(f?tw.w:tw.y);
#pragma unroll
      for(int t=0;t<2;t++)
#pragma unroll
        for(int e=0;e<2;e++){ const float vr=d[4*t+2*f+e], vi=d[4*(t+2)+2*f+e];
          sts32(yt+(4*e+2*t)*YT_S+f*32, pack_bf16(fmaf(vr,cc,-(vi*s)), fmaf(vr,s,vi*cc))); }
    }
  }
  STAMP(11);
  bar_sync(BAR_C,512);
  const int mp=warp&3, nt=(warp>>2)&1, mi=lane>>3, r=lane&7;
  const int s1g0=(g&3)*4+(g>>2);
  uint32_t av[2][8];
  if(warp<8){
    const uint4 B7=lds128(sb+CT_B7+lane*16);
    const uint32_t b70=nt?B7.z:B7.x, b71=nt?B7.w:B7.y;
    const uint32_t g0=lds32(sb+SM_MISC+64+s1g0*4), g1=lds32(sb+SM_MISC+72+s1g0*4);
    const uint32_t ya=sb+SM_BIG+c*(CH_AREA+32)+4096+g*YT_S+(16*mp)*4;
#pragma unroll
    for(int pp=0;pp<8;pp++){
      const uint2 lo=lds64(ya+pp*8), hi=lds64(ya+8*YT_S+pp*8);
      const uint32_t a0=lo.x, a2=lo.y, a1=hi.x, a3=hi.y;
      float y[4]; mma_bf16z(y,a0,a1,a2,a3,b70,b71);
      av[0][pp]=bmul(g0,pack_bf16(y[0],y[1])); av[1][pp]=bmul(g1,pack_bf16(y[2],y[3]));
    }
  } else {
    const uint32_t tag=lds32(sb+SM_MISC+252);
    mbar_wait(mb+MB_YB);
    const int t=tid-256;
    const uint4* src=p.yb+(size_t)cta*896+t;
    uint4 v[4]; int it=0; bool ok;
    do{ ok=true;
#pragma unroll
      for(int k=0;k<4;k++) if(k<3 || t<128){ v[k]=ld_rlx128(src+256*k); ok=ok&&((v[k].x&1u)==tag); }
    }while(!ok && ++it<SPIN_MAX);
#pragma unroll
    for(int k=0;k<4;k++) if(k<3 || t<128) sts128(sb+SM_YB+(t+256*k)*16,v[k].x,v[k].y,v[k].z,v[k].w);
  }
  bar_sync(BAR_C,512);
  STAMP(12);
  if(warp<8){
    const uint32_t o0=lds32(sb+SM_MISC+128+s1g0*4), o1=lds32(sb+SM_MISC+136+s1g0*4);
    const int dmin=min(64*(4*nt+(r>>1)),384)+16*mp+2*(mi>>1)+(r&1);
    const uint32_t yb=sb+SM_YB+(((2*dmin+(mi&1))^((((r>>1)&1)<<2)|(r>>2)))<<4);
#pragma unroll
    for(int pp=0;pp<8;pp+=2){
      uint32_t bv[4]; ldsm_x4t(bv[0],bv[1],bv[2],bv[3],yb+pp*64);
#pragma unroll
      for(int h=0;h<2;h++){ av[0][pp+h]=badd(av[0][pp+h],bmul(o0,bv[2*h])); av[1][pp+h]=badd(av[1][pp+h],bmul(o1,bv[2*h+1])); }
    }
    const bool odd=c&1;
    const int d1e=4*nt+(c&2);
#pragma unroll
    for(int f=0;f<2;f++){
      uint32_t rx[4];
#pragma unroll
      for(int k=0;k<4;k++) rx[k]=__shfl_xor_sync(0xffffffffu, odd?av[f][k]:av[f][4+k], 1);
      uint4* row=p.out+(128*(s1g0+2*f)+s2)*56+8*d1e+2*mp+(odd?1:0);
      *row = odd? make_uint4(rx[0],rx[1],rx[2],rx[3]) : make_uint4(av[f][0],av[f][1],av[f][2],av[f][3]);
      if(d1e+1<7) row[8] = odd? make_uint4(av[f][4],av[f][5],av[f][6],av[f][7]) : make_uint4(rx[0],rx[1],rx[2],rx[3]);
    }
  }
  STAMP(13);
}
}

extern "C" void kernel_launch(void* const* d_in, const int* in_sizes, int n_in, void* d_out, int out_size) {
  (void)in_sizes; (void)n_in; (void)out_size;
  static bool init=false;
  static void *aT,*aT2,*ayb,*axT,*async_,*atab;
  if(!init){ cudaFuncSetAttribute(fused_kernel,cudaFuncAttributeMaxDynamicSharedMemorySize,SM_TOTAL);
    cudaGetSymbolAddress(&aT,g_T); cudaGetSymbolAddress(&aT2,g_T2); cudaGetSymbolAddress(&ayb,g_yb); cudaGetSymbolAddress(&axT,g_xT); cudaGetSymbolAddress(&async_,g_sync); cudaGetSymbolAddress(&atab,g_tab);
    init=true; }
  Params p;
  p.T=(uint32_t*)aT; p.T2=(uint32_t*)aT2; p.yb=(uint4*)ayb; p.xT=(uint4*)axT; p.sync=(unsigned*)async_; p.tab=atab;
  p.x=(const __nv_bfloat16*)d_in[0]; p.wr=(const uint16_t*)d_in[1]; p.wi=(const uint16_t*)d_in[2];
  p.Are=(const uint32_t*)d_in[4]; p.Aim=(const uint32_t*)d_in[5]; p.Bre=(const uint32_t*)d_in[6]; p.Bim=(const uint32_t*)d_in[7];
  p.Cre=(const uint32_t*)d_in[8]; p.Cim=(const uint32_t*)d_in[9]; p.logdt=(const __nv_bfloat16*)d_in[10];
  p.dskip=(const uint16_t*)d_in[11]; p.gatew=(const uint4*)d_in[12]; p.out=(uint4*)d_out; p.id=0x3210u;
  fused_kernel<<<128,640,SM_TOTAL,cudaStreamPerThread>>>(p);
}
```
